```python
import torch

def _softmax(x, axis=-1):
    return torch.softmax(x, dim=axis)
def _gelu(x):
    return torch.nn.functional.gelu(x, approximate="tanh")
def _silu(x):
    return torch.nn.functional.silu(x)
def _sigmoid(x):
    return torch.sigmoid(x)
def _layernorm(x, axis=-1, eps=1e-5):
    m = x.mean(dim=axis, keepdim=True)
    v = x.var(dim=axis, keepdim=True, unbiased=False)
    return (x - m) / torch.sqrt(v + eps)
def _scatter_add(tgt, idx, src, axis=0):
    return tgt.clone().index_add_(axis, idx, src)
def _segment_sum(src, seg, n):
    out = torch.zeros((n,) + src.shape[1:], dtype=src.dtype)
    return out.index_add_(0, seg, src)
def _pad(x, pw):
    flat = tuple(v for pair in reversed(pw) for v in pair)
    return torch.nn.functional.pad(x, flat)

kernel_name = 'gated_mix__mha_block__mixer_s_mlp__prompt'

def setup_inputs():

    _w = (lambda a: (lambda t: t.to(torch.bfloat16) if t.is_floating_point() else t)(torch.as_tensor(a)))
    def _A_setup():
        B, S, D, H = 1, 2048, 1024, 32
        return {
            "x": _w((lambda *s: torch.randn(*s, dtype=torch.bfloat16) * 0.1)(B, S, D)),
            "wqkv": _w((lambda *s: torch.randn(*s, dtype=torch.bfloat16) * 0.4)(D, 3 * D)),
            "wo": _w((lambda *s: torch.randn(*s, dtype=torch.bfloat16) * 0.4)(D, D)),
        }
    _A_in = _A_setup()

    def _B_setup():
        B, S, D, F = 1, 2048, 1024, 3584
        return {
            "x":  _w((lambda *s: torch.randn(*s, dtype=torch.bfloat16) * 0.1)(B, S, D)),
            "w1": _w((lambda *s: torch.randn(*s, dtype=torch.bfloat16) * 3.2)(D, D) * (D ** -0.5)),
            "w2": _w((lambda *s: torch.randn(*s, dtype=torch.bfloat16) * 3.2)(D, D) * (D ** -0.5)),
            "w3": _w((lambda *s: torch.randn(*s, dtype=torch.bfloat16) * 3.2)(D, F) * (D ** -0.5)),
            "w4": _w((lambda *s: torch.randn(*s, dtype=torch.bfloat16) * 3.2)(F, D) * (F ** -0.5)),
        }
    _B_in = _B_setup()

    return {
        "A_x": _A_in["x"],
        "A_wqkv": _A_in["wqkv"],
        "A_wo": _A_in["wo"],
        "B_x": _B_in["x"],
        "B_w1": _B_in["w1"],
        "B_w2": _B_in["w2"],
        "B_w3": _B_in["w3"],
        "B_w4": _B_in["w4"],
        "gate_w": _w((lambda *s: torch.randn(*s, dtype=torch.bfloat16) * 0.4)(1024) * 16.0),
    }

def reference(A_x, A_wqkv, A_wo, B_x, B_w1, B_w2, B_w3, B_w4, gate_w):
    def _A_ref(x, wqkv, wo):
        B, S, D = x.shape
        H = 32
        Dh = D // H
        qkv = (lambda x, *d: x.permute(*d))((x @ wqkv).reshape(B, S, 3, H, Dh), 2, 0, 3, 1, 4)
        q, k, v = qkv[0], qkv[1], qkv[2]
        scores = torch.einsum("bhqd,bhkd->bhqk", q, k) * (Dh ** -0.5)
        p = _softmax(scores, axis=-1)
        o = torch.einsum("bhqk,bhkd->bhqd", p, v)
        return (lambda x, *d: x.permute(*d))(o, 0, 2, 1, 3).reshape(B, S, D) @ wo

    def _B_ref(x, w1, w2, w3, w4):
        B, S, D = x.shape
        h = _gelu(_layernorm(x, axis=-1) @ w1)
        c = D // 4
        g0 = _pad(h[:, :, 0*c:1*c], ((0, 0), (1, 0), (0, 0)))[:, :S, :]
        g1 = _pad(h[:, :, 1*c:2*c], ((0, 0), (0, 1), (0, 0)))[:, 1:, :]
        g2 = _pad(h[:, :, 2*c:3*c], ((0, 0), (2, 0), (0, 0)))[:, :S, :]
        g3 = _pad(h[:, :, 3*c:   ], ((0, 0), (0, 2), (0, 0)))[:, 2:, :]
        hs = torch.concatenate([g0, g1, g2, g3], axis=-1) @ w2
        x1 = x + hs
        h2 = _gelu(_layernorm(x1, axis=-1) @ w3) @ w4
        return x1 + h2

    x = A_x
    g = _sigmoid((x * gate_w).sum(-1, keepdims=True))
    a = _A_ref(x, A_wqkv, A_wo)
    b = _B_ref(x, B_w1, B_w2, B_w3, B_w4)
    return g * a + (1 - g) * b
```

```cpp
#include <cuda_runtime.h>
#include <cuda_bf16.h>
#include <cuda.h>
#include <stdint.h>

namespace {

constexpr int S_ = 2048;
constexpr int D_ = 1024;
constexpr int F_ = 3584;
constexpr int H_ = 32;
constexpr int DH_ = 32;

__device__ __align__(1024) __nv_bfloat16 g_qkv[S_ * 3 * D_];
__device__ __align__(1024) __nv_bfloat16 g_h[S_ * D_];
__device__ __align__(1024) __nv_bfloat16 g_x1[S_ * D_];
__device__ __align__(1024) __nv_bfloat16 g_hh[S_ * F_];
__device__ __align__(1024) __nv_bfloat16 g_o[S_ * D_];
__device__ __align__(16) float4 g_xstat[S_];
constexpr int CS_SPLIT = 8;
__device__ __align__(16) float g_cs[CS_SPLIT][D_ + F_];
__device__ __align__(16) float2 g_x1part[S_][8];

__device__ __forceinline__ uint32_t smem_u32(const void* p) {
    return (uint32_t)__cvta_generic_to_shared(p);
}
__device__ __forceinline__ void mbar_init(uint32_t bar, uint32_t count) {
    asm volatile("mbarrier.init.shared::cta.b64 [%0], %1;" ::"r"(bar), "r"(count) : "memory");
}
__device__ __forceinline__ void mbar_expect_tx(uint32_t bar, uint32_t bytes) {
    asm volatile("mbarrier.arrive.expect_tx.shared::cta.b64 _, [%0], %1;" ::"r"(bar), "r"(bytes) : "memory");
}
__device__ __forceinline__ void mbar_arrive(uint32_t bar) {
    asm volatile("mbarrier.arrive.shared::cta.b64 _, [%0];" ::"r"(bar) : "memory");
}
__device__ __forceinline__ void mbar_wait(uint32_t bar, uint32_t parity) {
    asm volatile(
        "{\n"
        ".reg .pred p;\n"
        "LAB_WAIT:\n"
        "mbarrier.try_wait.parity.shared::cta.b64 p, [%0], %1;\n"
        "@p bra LAB_DONE;\n"
        "bra LAB_WAIT;\n"
        "LAB_DONE:\n"
        "}\n" ::"r"(bar), "r"(parity) : "memory");
}
__device__ __forceinline__ void tma_load_2d(uint32_t dst, const CUtensorMap* map, int c0, int c1, uint32_t bar) {
    asm volatile(
        "cp.async.bulk.tensor.2d.shared::cluster.global.mbarrier::complete_tx::bytes [%0], [%1, {%3, %4}], [%2];"
        ::"r"(dst), "l"(reinterpret_cast<uint64_t>(map)), "r"(bar), "r"(c0), "r"(c1) : "memory");
}
__device__ __forceinline__ void tma_store_2d(const CUtensorMap* map, uint32_t src, int c0, int c1) {
    asm volatile(
        "cp.async.bulk.tensor.2d.global.shared::cta.bulk_group [%0, {%2, %3}], [%1];"
        ::"l"(reinterpret_cast<uint64_t>(map)), "r"(src), "r"(c0), "r"(c1) : "memory");
}
__device__ __forceinline__ void tma_store_commit() { asm volatile("cp.async.bulk.commit_group;" ::: "memory"); }
__device__ __forceinline__ void tma_store_wait0() { asm volatile("cp.async.bulk.wait_group 0;" ::: "memory"); }
__device__ __forceinline__ void prefetch_tmap(const CUtensorMap* map) {
    asm volatile("prefetch.tensormap [%0];" ::"l"(reinterpret_cast<uint64_t>(map)) : "memory");
}
__device__ __forceinline__ void fence_proxy_async() { asm volatile("fence.proxy.async.shared::cta;" ::: "memory"); }
__device__ __forceinline__ void fence_mbar_init() { asm volatile("fence.mbarrier_init.release.cluster;" ::: "memory"); }
__device__ __forceinline__ void wgmma_fence() { asm volatile("wgmma.fence.sync.aligned;" ::: "memory"); }
__device__ __forceinline__ void wgmma_commit() { asm volatile("wgmma.commit_group.sync.aligned;" ::: "memory"); }
template <int N>
__device__ __forceinline__ void wgmma_wait() { asm volatile("wgmma.wait_group.sync.aligned %0;" ::"n"(N) : "memory"); }
__device__ __forceinline__ void named_bar_sync(int id, int n) { asm volatile("bar.sync %0, %1;" ::"r"(id), "r"(n) : "memory"); }
__device__ __forceinline__ void pdl_wait() { asm volatile("griddepcontrol.wait;" ::: "memory"); }
__device__ __forceinline__ void pdl_launch() { asm volatile("griddepcontrol.launch_dependents;" ::: "memory"); }
template <int N>
__device__ __forceinline__ void reg_alloc() { asm volatile("setmaxnreg.inc.sync.aligned.u32 %0;" ::"n"(N)); }
template <int N>
__device__ __forceinline__ void reg_dealloc() { asm volatile("setmaxnreg.dec.sync.aligned.u32 %0;" ::"n"(N)); }

__device__ __forceinline__ uint64_t make_desc(uint32_t addr, uint32_t lbo_bytes, uint32_t sbo_bytes, uint32_t layout) {
    uint64_t d = 0;
    d |= (uint64_t)((addr & 0x3FFFF) >> 4);
    d |= (uint64_t)((lbo_bytes >> 4) & 0x3FFF) << 16;
    d |= (uint64_t)((sbo_bytes >> 4) & 0x3FFF) << 32;
    d |= (uint64_t)layout << 62;
    return d;
}
constexpr uint32_t SW128 = 1, SW64 = 2;

__device__ __forceinline__ uint32_t pack_bf16(float lo, float hi) {
    uint32_t r;
    asm("cvt.rn.bf16x2.f32 %0, %1, %2;" : "=r"(r) : "f"(hi), "f"(lo));
    return r;
}
__device__ __forceinline__ float bf16_lo(uint32_t v) { return __uint_as_float(v << 16); }
__device__ __forceinline__ float bf16_hi(uint32_t v) { return __uint_as_float(v & 0xFFFF0000u); }
__device__ __forceinline__ float ex2(float x) {
    float r;
    asm("ex2.approx.ftz.f32 %0, %1;" : "=f"(r) : "f"(x));
    return r;
}
__device__ __forceinline__ float tanh_approx(float x) {
    float r;
    asm("tanh.approx.f32 %0, %1;" : "=f"(r) : "f"(x));
    return r;
}
__device__ __forceinline__ float gelu_tanh(float v) {
    float u = v * (0.7978845608028654f + 0.0356774081363001f * v * v);
    float hv = 0.5f * v;
    return fmaf(hv, tanh_approx(u), hv);
}
__device__ __forceinline__ void stmatrix_x4(uint32_t addr, uint32_t r0, uint32_t r1, uint32_t r2, uint32_t r3) {
    asm volatile("stmatrix.sync.aligned.m8n8.x4.shared.b16 [%0], {%1, %2, %3, %4};"
                 ::"r"(addr), "r"(r0), "r"(r1), "r"(r2), "r"(r3) : "memory");
}

#define ACC8(a, o) "+f"(a[o + 0]), "+f"(a[o + 1]), "+f"(a[o + 2]), "+f"(a[o + 3]), "+f"(a[o + 4]), "+f"(a[o + 5]), "+f"(a[o + 6]), "+f"(a[o + 7])

template <int TB>
__device__ __forceinline__ void wgmma_m64n128k16_ss(float (&d)[64], uint64_t da, uint64_t db, int scale_d) {
    asm volatile(
        "{\n"
        ".reg .pred p;\n"
        "setp.ne.b32 p, %66, 0;\n"
        "wgmma.mma_async.sync.aligned.m64n128k16.f32.bf16.bf16 "
        "{%0, %1, %2, %3, %4, %5, %6, %7, %8, %9, %10, %11, %12, %13, %14, %15, "
        "%16, %17, %18, %19, %20, %21, %22, %23, %24, %25, %26, %27, %28, %29, %30, %31, "
        "%32, %33, %34, %35, %36, %37, %38, %39, %40, %41, %42, %43, %44, %45, %46, %47, "
        "%48, %49, %50, %51, %52, %53, %54, %55, %56, %57, %58, %59, %60, %61, %62, %63}, "
        "%64, %65, p, 1, 1, 0, %67;\n"
        "}\n"
        : ACC8(d, 0), ACC8(d, 8), ACC8(d, 16), ACC8(d, 24), ACC8(d, 32), ACC8(d, 40), ACC8(d, 48), ACC8(d, 56)
        : "l"(da), "l"(db), "r"(scale_d), "n"(TB));
}

__device__ __forceinline__ void wgmma_m64n32k16_rs(float (&d)[16], uint32_t a0, uint32_t a1, uint32_t a2, uint32_t a3,
                                                   uint64_t db) {
    asm volatile(
        "{\n"
        "wgmma.mma_async.sync.aligned.m64n32k16.f32.bf16.bf16 "
        "{%0, %1, %2, %3, %4, %5, %6, %7, %8, %9, %10, %11, %12, %13, %14, %15}, "
        "{%16, %17, %18, %19}, %20, 1, 1, 1, 1;\n"
        "}\n"
        : ACC8(d, 0), ACC8(d, 8)
        : "r"(a0), "r"(a1), "r"(a2), "r"(a3), "l"(db));
}

constexpr int PREP_ROW_BLOCKS = S_ / 8;
constexpr int PREP_CS_BLOCKS = ((D_ + F_) / 256) * CS_SPLIT;

__global__ void __launch_bounds__(256) prep_kernel(const __nv_bfloat16* __restrict__ x,
                                                   const __nv_bfloat16* __restrict__ gate_w,
                                                   const __nv_bfloat16* __restrict__ w1,
                                                   const __nv_bfloat16* __restrict__ w3) {
    pdl_launch();
    const int tid = threadIdx.x;
    if (blockIdx.x < PREP_CS_BLOCKS) {
        __shared__ float red[8][256];
        const int cb = blockIdx.x / CS_SPLIT, ks = blockIdx.x % CS_SPLIT;
        const __nv_bfloat16* w;
        int ld, col0;
        if (cb < D_ / 256) { w = w1; ld = D_; col0 = cb * 256; }
        else { w = w3; ld = F_; col0 = (cb - D_ / 256) * 256; }
        const int cg = tid & 31, rg = tid >> 5;
        const int row0 = ks * (D_ / CS_SPLIT) + rg * 16;
        float s[8];
#pragma unroll
        for (int i = 0; i < 8; i++) s[i] = 0.f;
        const uint4* p = reinterpret_cast<const uint4*>(w + (size_t)row0 * ld + col0 + cg * 8);
        uint4 v[16];
#pragma unroll
        for (int r = 0; r < 16; r++) v[r] = __ldg(p + (size_t)r * (ld / 8));
#pragma unroll
        for (int r = 0; r < 16; r++) {
            s[0] += bf16_lo(v[r].x); s[1] += bf16_hi(v[r].x);
            s[2] += bf16_lo(v[r].y); s[3] += bf16_hi(v[r].y);
            s[4] += bf16_lo(v[r].z); s[5] += bf16_hi(v[r].z);
            s[6] += bf16_lo(v[r].w); s[7] += bf16_hi(v[r].w);
        }
#pragma unroll
        for (int i = 0; i < 8; i++) red[rg][cg * 8 + i] = s[i];
        __syncthreads();
        float t = 0.f;
#pragma unroll
        for (int i = 0; i < 8; i++) t += red[i][tid];
        g_cs[ks][cb * 256 + tid] = t;
    } else {
        const int row = (blockIdx.x - PREP_CS_BLOCKS) * 8 + (tid >> 5);
        const int lane = tid & 31;
        const uint4* p = reinterpret_cast<const uint4*>(x + (size_t)row * D_);
        const uint4* gw = reinterpret_cast<const uint4*>(gate_w);
        float v[32];
        float sum = 0.f, dot = 0.f;
#pragma unroll
        for (int i = 0; i < 4; i++) {
            uint4 a = __ldg(p + i * 32 + lane);
            uint4 b = __ldg(gw + i * 32 + lane);
            v[i * 8 + 0] = bf16_lo(a.x); v[i * 8 + 1] = bf16_hi(a.x);
            v[i * 8 + 2] = bf16_lo(a.y); v[i * 8 + 3] = bf16_hi(a.y);
            v[i * 8 + 4] = bf16_lo(a.z); v[i * 8 + 5] = bf16_hi(a.z);
            v[i * 8 + 6] = bf16_lo(a.w); v[i * 8 + 7] = bf16_hi(a.w);
            dot += v[i * 8 + 0] * bf16_lo(b.x) + v[i * 8 + 1] * bf16_hi(b.x);
            dot += v[i * 8 + 2] * bf16_lo(b.y) + v[i * 8 + 3] * bf16_hi(b.y);
            dot += v[i * 8 + 4] * bf16_lo(b.z) + v[i * 8 + 5] * bf16_hi(b.z);
            dot += v[i * 8 + 6] * bf16_lo(b.w) + v[i * 8 + 7] * bf16_hi(b.w);
        }
#pragma unroll
        for (int i = 0; i < 32; i++) sum += v[i];
#pragma unroll
        for (int o = 16; o > 0; o >>= 1) {
            sum += __shfl_xor_sync(0xffffffffu, sum, o);
            dot += __shfl_xor_sync(0xffffffffu, dot, o);
        }
        const float mean = sum * (1.f / D_);
        float m2 = 0.f;
#pragma unroll
        for (int i = 0; i < 32; i++) { float d = v[i] - mean; m2 += d * d; }
#pragma unroll
        for (int o = 16; o > 0; o >>= 1) m2 += __shfl_xor_sync(0xffffffffu, m2, o);
        if (lane == 0) {
            float rstd = rsqrtf(m2 * (1.f / D_) + 1e-5f);
            float g = 1.f / (1.f + __expf(-dot));
            float og = 1.f / (1.f + __expf(dot));
            g_xstat[row] = make_float4(mean, rstd, g, og);
        }
    }
}

constexpr int BM = 128, BN = 128, BK = 64;
constexpr int G_STAGES = 3;
constexpr int A_STAGE_BYTES = BM * BK * 2;
constexpr int B_STAGE_BYTES = BK * BN * 2;
constexpr int STAGE_BYTES = A_STAGE_BYTES + B_STAGE_BYTES;
constexpr int G_SMEM = G_STAGES * STAGE_BYTES + 1024   + 1024  ;

template <int MODE>
__global__ void __launch_bounds__(288, 2)
gemm_kernel(const __grid_constant__ CUtensorMap tmA0, const __grid_constant__ CUtensorMap tmA1,
            const __grid_constant__ CUtensorMap tmB0, const __grid_constant__ CUtensorMap tmB1,
            const __grid_constant__ CUtensorMap tmC0, const __grid_constant__ CUtensorMap tmC1,
            const __nv_bfloat16* __restrict__ xres) {
    constexpr int NK = (MODE == 4) ? (F_ + D_) / BK : D_ / BK;
    constexpr int KSPLIT = F_ / BK;

    extern __shared__ uint8_t smem_raw[];
    const uint32_t smem_base = (smem_u32(smem_raw) + 1023u) & ~1023u;
    uint8_t* smem_gen = smem_raw + (smem_base - smem_u32(smem_raw));
    const uint32_t bar_base = smem_base + G_STAGES * STAGE_BYTES;
    float* s_cs = reinterpret_cast<float*>(smem_gen + G_STAGES * STAGE_BYTES + 128);

    const int tid = threadIdx.x;
    const int wg = tid >> 7;
    const int m_tile = blockIdx.x & 15;
    const int n_tile = blockIdx.x >> 4;
    const int m0 = m_tile * BM;
    const int n0 = n_tile * BN;

    if (tid == 0) {
#pragma unroll
        for (int s = 0; s < G_STAGES; s++) {
            mbar_init(bar_base + 8 * s, 1);
            mbar_init(bar_base + 8 * (G_STAGES + s), 8);
        }
        fence_mbar_init();
    }
    __syncthreads();

    if (wg == 2) {
        if (tid == 256) {
            if (MODE != 1) pdl_wait();
            pdl_launch();
            for (int it = 0; it < NK; it++) {
                const int s = it % G_STAGES;
                const uint32_t ph = (it / G_STAGES) & 1;
                mbar_wait(bar_base + 8 * (G_STAGES + s), ph ^ 1);
                const uint32_t full = bar_base + 8 * s;
                mbar_expect_tx(full, STAGE_BYTES);
                const uint32_t sa = smem_base + s * STAGE_BYTES;
                const uint32_t sb = sa + A_STAGE_BYTES;
                if (MODE == 1) {
                    tma_load_2d(sa, &tmA0, it * BK, m0, full);
                    if (n0 < 3 * D_) {
                        tma_load_2d(sb, &tmB0, n0, it * BK, full);
                        tma_load_2d(sb + 8192, &tmB0, n0 + 64, it * BK, full);
                    } else {
                        tma_load_2d(sb, &tmB1, n0 - 3 * D_, it * BK, full);
                        tma_load_2d(sb + 8192, &tmB1, n0 - 3 * D_ + 64, it * BK, full);
                    }
                } else if (MODE == 2) {
                    const int q = it >> 2;
                    const int sh = (q == 0) ? -1 : (q == 1) ? 1 : (q == 2) ? -2 : 2;
                    tma_load_2d(sa, &tmA0, it * BK, m0 + sh, full);
                    tma_load_2d(sb, &tmB0, n0, it * BK, full);
                    tma_load_2d(sb + 8192, &tmB0, n0 + 64, it * BK, full);
                } else if (MODE == 3) {
                    tma_load_2d(sa, &tmA0, it * BK, m0, full);
                    tma_load_2d(sb, &tmB0, n0, it * BK, full);
                    tma_load_2d(sb + 8192, &tmB0, n0 + 64, it * BK, full);
                } else {
                    if (it < KSPLIT) {
                        tma_load_2d(sa, &tmA0, it * BK, m0, full);
                        tma_load_2d(sb, &tmB0, n0, it * BK, full);
                        tma_load_2d(sb + 8192, &tmB0, n0 + 64, it * BK, full);
                    } else {
                        const int k0 = (it - KSPLIT) * BK;
                        tma_load_2d(sa, &tmA1, k0, m0, full);
                        tma_load_2d(sb, &tmB1, n0, k0, full);
                        tma_load_2d(sb + 8192, &tmB1, n0 + 64, k0, full);
                    }
                }
            }
        }
    } else {
        const int cw = wg;
        const int warp = (tid >> 5) & 3;
        const int lane = tid & 31;
        float acc[64];
#pragma unroll
        for (int i = 0; i < 64; i++) acc[i] = 0.f;

        for (int it = 0; it < NK; it++) {
            const int s = it % G_STAGES;
            const uint32_t ph = (it / G_STAGES) & 1;
            mbar_wait(bar_base + 8 * s, ph);
            const uint32_t sa = smem_base + s * STAGE_BYTES + cw * 8192;
            const uint32_t sb = smem_base + s * STAGE_BYTES + A_STAGE_BYTES;
            wgmma_fence();
#pragma unroll
            for (int k = 0; k < 4; k++) {
                uint64_t da = make_desc(sa + k * 32, 16, 1024, SW128);
                uint64_t db = make_desc(sb + k * 2048, 8192, 1024, SW128);
                wgmma_m64n128k16_ss<1>(acc, da, db, (it | k) != 0);
            }
            wgmma_commit();
            wgmma_wait<1>();
            if (it > 0 && lane == 0) mbar_arrive(bar_base + 8 * (G_STAGES + (it - 1) % G_STAGES));
        }
        wgmma_wait<0>();

        pdl_wait();
        const int r0 = m0 + cw * 64 + warp * 16 + (lane >> 2);
        const int r1 = r0 + 8;
        const int cq = (lane & 3) * 2;
        const bool use_cs = (MODE == 3) || (MODE == 1 && n0 >= 3 * D_);
        if (use_cs) {
            const int ct = tid;
            if (ct < BN) {
                const int col = (MODE == 1) ? (n0 - 3 * D_ + ct) : (D_ + n0 + ct);
                float t = 0.f;
#pragma unroll
                for (int i = 0; i < CS_SPLIT; i++) t += g_cs[i][col];
                s_cs[ct] = t;
            }
        }
        named_bar_sync(1, 256);

        if (MODE == 1) {
            if (n0 >= 3 * D_) {
                const float4 st0 = g_xstat[r0], st1 = g_xstat[r1];
#pragma unroll
                for (int j = 0; j < 16; j++) {
                    const float2 cs = *reinterpret_cast<const float2*>(&s_cs[j * 8 + cq]);
                    acc[4 * j + 0] = gelu_tanh(st0.y * (acc[4 * j + 0] - st0.x * cs.x));
                    acc[4 * j + 1] = gelu_tanh(st0.y * (acc[4 * j + 1] - st0.x * cs.y));
                    acc[4 * j + 2] = gelu_tanh(st1.y * (acc[4 * j + 2] - st1.x * cs.x));
                    acc[4 * j + 3] = gelu_tanh(st1.y * (acc[4 * j + 3] - st1.x * cs.y));
                }
            }
        } else if (MODE == 2) {
            const uint32_t* x0 = reinterpret_cast<const uint32_t*>(xres + (size_t)r0 * D_ + n0 + cq);
            const uint32_t* x1 = reinterpret_cast<const uint32_t*>(xres + (size_t)r1 * D_ + n0 + cq);
            float s0 = 0.f, s1 = 0.f;
#pragma unroll
            for (int j = 0; j < 16; j++) {
                const uint32_t a = __ldg(x0 + j * 4), b = __ldg(x1 + j * 4);
                uint32_t p0 = pack_bf16(acc[4 * j + 0] + bf16_lo(a), acc[4 * j + 1] + bf16_hi(a));
                uint32_t p1 = pack_bf16(acc[4 * j + 2] + bf16_lo(b), acc[4 * j + 3] + bf16_hi(b));
                acc[4 * j + 0] = bf16_lo(p0); acc[4 * j + 1] = bf16_hi(p0);
                acc[4 * j + 2] = bf16_lo(p1); acc[4 * j + 3] = bf16_hi(p1);
                s0 += acc[4 * j + 0] + acc[4 * j + 1];
                s1 += acc[4 * j + 2] + acc[4 * j + 3];
            }
            s0 += __shfl_xor_sync(0xffffffffu, s0, 1); s0 += __shfl_xor_sync(0xffffffffu, s0, 2);
            s1 += __shfl_xor_sync(0xffffffffu, s1, 1); s1 += __shfl_xor_sync(0xffffffffu, s1, 2);
            const float mu0 = s0 * (1.f / BN), mu1 = s1 * (1.f / BN);
            float q0 = 0.f, q1 = 0.f;
#pragma unroll
            for (int j = 0; j < 16; j++) {
                float d;
                d = acc[4 * j + 0] - mu0; q0 += d * d;
                d = acc[4 * j + 1] - mu0; q0 += d * d;
                d = acc[4 * j + 2] - mu1; q1 += d * d;
                d = acc[4 * j + 3] - mu1; q1 += d * d;
            }
            q0 += __shfl_xor_sync(0xffffffffu, q0, 1); q0 += __shfl_xor_sync(0xffffffffu, q0, 2);
            q1 += __shfl_xor_sync(0xffffffffu, q1, 1); q1 += __shfl_xor_sync(0xffffffffu, q1, 2);
            if ((lane & 3) == 0) {
                g_x1part[r0][n_tile] = make_float2(s0, q0);
                g_x1part[r1][n_tile] = make_float2(s1, q1);
            }
        } else if (MODE == 3) {
            float mean[2], rstd[2], og[2];
#pragma unroll
            for (int h = 0; h < 2; h++) {
                const int r = h ? r1 : r0;
                const float4* pp = reinterpret_cast<const float4*>(&g_x1part[r][0]);
                float4 a = pp[0], b = pp[1], c = pp[2], d = pp[3];
                float tot = a.x + a.z + b.x + b.z + c.x + c.z + d.x + d.z;
                float mu = tot * (1.f / D_);
                float m2 = a.y + a.w + b.y + b.w + c.y + c.w + d.y + d.w;
                float e;
                e = a.x * (1.f / 128) - mu; m2 += 128.f * e * e;
                e = a.z * (1.f / 128) - mu; m2 += 128.f * e * e;
                e = b.x * (1.f / 128) - mu; m2 += 128.f * e * e;
                e = b.z * (1.f / 128) - mu; m2 += 128.f * e * e;
                e = c.x * (1.f / 128) - mu; m2 += 128.f * e * e;
                e = c.z * (1.f / 128) - mu; m2 += 128.f * e * e;
                e = d.x * (1.f / 128) - mu; m2 += 128.f * e * e;
                e = d.z * (1.f / 128) - mu; m2 += 128.f * e * e;
                mean[h] = mu;
                rstd[h] = rsqrtf(m2 * (1.f / D_) + 1e-5f);
                og[h] = g_xstat[r].w;
            }
#pragma unroll
            for (int j = 0; j < 16; j++) {
                const float2 cs = *reinterpret_cast<const float2*>(&s_cs[j * 8 + cq]);
                acc[4 * j + 0] = og[0] * gelu_tanh(rstd[0] * (acc[4 * j + 0] - mean[0] * cs.x));
                acc[4 * j + 1] = og[0] * gelu_tanh(rstd[0] * (acc[4 * j + 1] - mean[0] * cs.y));
                acc[4 * j + 2] = og[1] * gelu_tanh(rstd[1] * (acc[4 * j + 2] - mean[1] * cs.x));
                acc[4 * j + 3] = og[1] * gelu_tanh(rstd[1] * (acc[4 * j + 3] - mean[1] * cs.y));
            }
        } else {
            const float og0 = g_xstat[r0].w, og1 = g_xstat[r1].w;
            const uint32_t* x0 = reinterpret_cast<const uint32_t*>(g_x1 + (size_t)r0 * D_ + n0 + cq);
            const uint32_t* x1 = reinterpret_cast<const uint32_t*>(g_x1 + (size_t)r1 * D_ + n0 + cq);
#pragma unroll
            for (int j = 0; j < 16; j++) {
                const uint32_t a = x0[j * 4], b = x1[j * 4];
                acc[4 * j + 0] += og0 * bf16_lo(a);
                acc[4 * j + 1] += og0 * bf16_hi(a);
                acc[4 * j + 2] += og1 * bf16_lo(b);
                acc[4 * j + 3] += og1 * bf16_hi(b);
            }
        }

        const uint32_t so = smem_base + cw * 16384;
        {
            const int mrow = warp * 16 + (lane & 7) + ((lane >> 3) & 1) * 8;
            const int mcol = lane >> 4;
#pragma unroll
            for (int jj = 0; jj < 8; jj++) {
                const int chunk = (jj & 3) * 2 + mcol;
                const uint32_t addr = so + (jj >> 2) * 8192 + mrow * 128 + ((chunk ^ (mrow & 7)) << 4);
                stmatrix_x4(addr, pack_bf16(acc[8 * jj + 0], acc[8 * jj + 1]), pack_bf16(acc[8 * jj + 2], acc[8 * jj + 3]),
                            pack_bf16(acc[8 * jj + 4], acc[8 * jj + 5]), pack_bf16(acc[8 * jj + 6], acc[8 * jj + 7]));
            }
        }
        fence_proxy_async();
        named_bar_sync(2 + cw, 128);
        if ((tid & 127) == 0) {
            const CUtensorMap* mc = &tmC0;
            int c0 = n0;
            if (MODE == 1 && n0 >= 3 * D_) { mc = &tmC1; c0 = n0 - 3 * D_; }
            tma_store_2d(mc, so, c0, m0 + cw * 64);
            tma_store_2d(mc, so + 8192, c0 + 64, m0 + cw * 64);
            tma_store_commit();
            tma_store_wait0();
        }
    }
}

constexpr int A_NWG = 4;
constexpr int A_BQ = 64 * A_NWG;
constexpr int A_BKV = 128;
constexpr int A_STAGES = 3;
constexpr int A_KV_BYTES = A_BKV * DH_ * 2;
constexpr int A_Q_BYTES = 64 * DH_ * 2;
constexpr int A_SMEM = A_NWG * A_Q_BYTES + 2 * A_STAGES * A_KV_BYTES + 1024 + 256;
constexpr int A_THREADS = A_NWG * 128 + 32;

__global__ void __launch_bounds__(A_THREADS, 1)
attn_kernel(const __grid_constant__ CUtensorMap tmQ, const __grid_constant__ CUtensorMap tmKV) {
    extern __shared__ uint8_t smem_raw[];
    const uint32_t smem_base = (smem_u32(smem_raw) + 1023u) & ~1023u;
    const uint32_t sQ = smem_base;
    const uint32_t sK = sQ + A_NWG * A_Q_BYTES;
    const uint32_t sV = sK + A_STAGES * A_KV_BYTES;
    const uint32_t bar = sV + A_STAGES * A_KV_BYTES;
    const uint32_t bar_q = bar;
    const uint32_t bar_kf = bar + 8;
    const uint32_t bar_vf = bar_kf + 8 * A_STAGES;
    const uint32_t bar_ke = bar_vf + 8 * A_STAGES;
    const uint32_t bar_ve = bar_ke + 8 * A_STAGES;

    const int tid = threadIdx.x;
    const int head = blockIdx.x & 31;
    const int qb = blockIdx.x >> 5;
    const int q0 = qb * A_BQ;
    constexpr int NT = S_ / A_BKV;

    if (tid == 0) {
        mbar_init(bar_q, 1);
#pragma unroll
        for (int s = 0; s < A_STAGES; s++) {
            mbar_init(bar_kf + 8 * s, 1);
            mbar_init(bar_vf + 8 * s, 1);
            mbar_init(bar_ke + 8 * s, A_NWG * 4);
            mbar_init(bar_ve + 8 * s, A_NWG * 4);
        }
        fence_mbar_init();
    }
    __syncthreads();

    if (tid >= A_NWG * 128) {
        if (tid == A_NWG * 128) {
            pdl_wait();
            pdl_launch();
            mbar_expect_tx(bar_q, A_NWG * A_Q_BYTES);
#pragma unroll
            for (int w = 0; w < A_NWG; w++) tma_load_2d(sQ + w * A_Q_BYTES, &tmQ, head * DH_, q0 + w * 64, bar_q);
            for (int t = 0; t < NT; t++) {
                const int s = t % A_STAGES;
                const uint32_t ph = (t / A_STAGES) & 1;
                mbar_wait(bar_ke + 8 * s, ph ^ 1);
                mbar_expect_tx(bar_kf + 8 * s, A_KV_BYTES);
                tma_load_2d(sK + s * A_KV_BYTES, &tmKV, D_ + head * DH_, t * A_BKV, bar_kf + 8 * s);
                mbar_wait(bar_ve + 8 * s, ph ^ 1);
                mbar_expect_tx(bar_vf + 8 * s, A_KV_BYTES);
                tma_load_2d(sV + s * A_KV_BYTES, &tmKV, 2 * D_ + head * DH_, t * A_BKV, bar_vf + 8 * s);
            }
        }
    } else {
        const int wg = tid >> 7;
        const int warp = (tid >> 5) & 3;
        const int lane = tid & 31;
        const float cscale = 0.17677669529663687f * 1.4426950408889634f;
        float o[16];
#pragma unroll
        for (int i = 0; i < 16; i++) o[i] = 0.f;
        float m0v = -INFINITY, m1v = -INFINITY, l0 = 0.f, l1 = 0.f;
        const uint32_t qa = sQ + wg * A_Q_BYTES;
        mbar_wait(bar_q, 0);

        for (int t = 0; t < NT; t++) {
            const int s = t % A_STAGES;
            const uint32_t ph = (t / A_STAGES) & 1;
            float sc[64];
            mbar_wait(bar_kf + 8 * s, ph);
            wgmma_fence();
#pragma unroll
            for (int k = 0; k < 2; k++) {
                uint64_t da = make_desc(qa + k * 32, 16, 512, SW64);
                uint64_t db = make_desc(sK + s * A_KV_BYTES + k * 32, 16, 512, SW64);
                wgmma_m64n128k16_ss<0>(sc, da, db, k);
            }
            wgmma_commit();
            wgmma_wait<0>();
            if (lane == 0) mbar_arrive(bar_ke + 8 * s);

            float mx0 = sc[0], mx1 = sc[2];
#pragma unroll
            for (int j = 0; j < 16; j++) {
                mx0 = fmaxf(mx0, fmaxf(sc[4 * j + 0], sc[4 * j + 1]));
                mx1 = fmaxf(mx1, fmaxf(sc[4 * j + 2], sc[4 * j + 3]));
            }
            mx0 = fmaxf(mx0, __shfl_xor_sync(0xffffffffu, mx0, 1));
            mx0 = fmaxf(mx0, __shfl_xor_sync(0xffffffffu, mx0, 2));
            mx1 = fmaxf(mx1, __shfl_xor_sync(0xffffffffu, mx1, 1));
            mx1 = fmaxf(mx1, __shfl_xor_sync(0xffffffffu, mx1, 2));
            const float mn0 = fmaxf(m0v, mx0), mn1 = fmaxf(m1v, mx1);
            const float al0 = ex2((m0v - mn0) * cscale), al1 = ex2((m1v - mn1) * cscale);
            m0v = mn0; m1v = mn1;
            const float mb0 = mn0 * cscale, mb1 = mn1 * cscale;
            uint32_t p[32];
            float rs0 = 0.f, rs1 = 0.f;
#pragma unroll
            for (int j = 0; j < 16; j++) {
                float e0 = ex2(fmaf(sc[4 * j + 0], cscale, -mb0));
                float e1 = ex2(fmaf(sc[4 * j + 1], cscale, -mb0));
                float e2 = ex2(fmaf(sc[4 * j + 2], cscale, -mb1));
                float e3 = ex2(fmaf(sc[4 * j + 3], cscale, -mb1));
                rs0 += e0 + e1;
                rs1 += e2 + e3;
                p[2 * j + 0] = pack_bf16(e0, e1);
                p[2 * j + 1] = pack_bf16(e2, e3);
            }
            l0 = l0 * al0 + rs0;
            l1 = l1 * al1 + rs1;
#pragma unroll
            for (int j = 0; j < 4; j++) {
                o[4 * j + 0] *= al0; o[4 * j + 1] *= al0;
                o[4 * j + 2] *= al1; o[4 * j + 3] *= al1;
            }
            mbar_wait(bar_vf + 8 * s, ph);
            wgmma_fence();
#pragma unroll
            for (int k = 0; k < 8; k++) {
                uint64_t db = make_desc(sV + s * A_KV_BYTES + k * 1024, 0, 512, SW64);
                wgmma_m64n32k16_rs(o, p[4 * k + 0], p[4 * k + 1], p[4 * k + 2], p[4 * k + 3], db);
            }
            wgmma_commit();
            wgmma_wait<0>();
            if (lane == 0) mbar_arrive(bar_ve + 8 * s);
        }
        l0 += __shfl_xor_sync(0xffffffffu, l0, 1); l0 += __shfl_xor_sync(0xffffffffu, l0, 2);
        l1 += __shfl_xor_sync(0xffffffffu, l1, 1); l1 += __shfl_xor_sync(0xffffffffu, l1, 2);
        const int r0 = q0 + wg * 64 + warp * 16 + (lane >> 2);
        const int r1 = r0 + 8;
        const float f0 = g_xstat[r0].z / l0, f1 = g_xstat[r1].z / l1;
        uint32_t* d0 = reinterpret_cast<uint32_t*>(g_o + (size_t)r0 * D_ + head * DH_ + (lane & 3) * 2);
        uint32_t* d1 = reinterpret_cast<uint32_t*>(g_o + (size_t)r1 * D_ + head * DH_ + (lane & 3) * 2);
#pragma unroll
        for (int j = 0; j < 4; j++) {
            d0[j * 4] = pack_bf16(o[4 * j + 0] * f0, o[4 * j + 1] * f0);
            d1[j * 4] = pack_bf16(o[4 * j + 2] * f1, o[4 * j + 3] * f1);
        }
    }
}

typedef CUresult (*PFN_encodeTiled)(CUtensorMap*, CUtensorMapDataType, cuuint32_t, void*, const cuuint64_t*,
                                    const cuuint64_t*, const cuuint32_t*, const cuuint32_t*, CUtensorMapInterleave,
                                    CUtensorMapSwizzle, CUtensorMapL2promotion, CUtensorMapFloatOOBfill);

CUtensorMap make_map(PFN_encodeTiled enc, const void* ptr, uint64_t inner, uint64_t outer, uint32_t box_inner,
                     uint32_t box_outer, CUtensorMapSwizzle sw) {
    CUtensorMap m;
    cuuint64_t dims[2] = {inner, outer};
    cuuint64_t strides[1] = {inner * 2};
    cuuint32_t box[2] = {box_inner, box_outer};
    cuuint32_t es[2] = {1, 1};
    enc(&m, CU_TENSOR_MAP_DATA_TYPE_BFLOAT16, 2, const_cast<void*>(ptr), dims, strides, box, es,
        CU_TENSOR_MAP_INTERLEAVE_NONE, sw, CU_TENSOR_MAP_L2_PROMOTION_L2_256B, CU_TENSOR_MAP_FLOAT_OOB_FILL_NONE);
    return m;
}

template <typename... KArgs, typename... Args>
void launch(void (*kern)(KArgs...), int grid, int block, int smem, cudaStream_t st, bool pdl, Args&&... args) {
    cudaLaunchConfig_t cfg = {};
    cfg.gridDim = dim3(grid);
    cfg.blockDim = dim3(block);
    cfg.dynamicSmemBytes = smem;
    cfg.stream = st;
    cudaLaunchAttribute at[1];
    at[0].id = cudaLaunchAttributeProgrammaticStreamSerialization;
    at[0].val.programmaticStreamSerializationAllowed = 1;
    cfg.attrs = at;
    cfg.numAttrs = pdl ? 1 : 0;
    cudaLaunchKernelEx(&cfg, kern, KArgs(args)...);
}

}

extern "C" void kernel_launch(void* const* d_in, const int* in_sizes, int n_in, void* d_out, int out_size) {
    const __nv_bfloat16* x = (const __nv_bfloat16*)d_in[0];
    const __nv_bfloat16* wqkv = (const __nv_bfloat16*)d_in[1];
    const __nv_bfloat16* wo = (const __nv_bfloat16*)d_in[2];
    const __nv_bfloat16* w1 = (const __nv_bfloat16*)d_in[4];
    const __nv_bfloat16* w2 = (const __nv_bfloat16*)d_in[5];
    const __nv_bfloat16* w3 = (const __nv_bfloat16*)d_in[6];
    const __nv_bfloat16* w4 = (const __nv_bfloat16*)d_in[7];
    const __nv_bfloat16* gate_w = (const __nv_bfloat16*)d_in[8];

    void* fn = nullptr;
    cudaDriverEntryPointQueryResult qres;
    cudaGetDriverEntryPoint("cuTensorMapEncodeTiled", &fn, cudaEnableDefault, &qres);
    PFN_encodeTiled enc = (PFN_encodeTiled)fn;

    void *p_qkv, *p_h, *p_x1, *p_hh, *p_o;
    cudaGetSymbolAddress(&p_qkv, g_qkv);
    cudaGetSymbolAddress(&p_h, g_h);
    cudaGetSymbolAddress(&p_x1, g_x1);
    cudaGetSymbolAddress(&p_hh, g_hh);
    cudaGetSymbolAddress(&p_o, g_o);

    const CUtensorMapSwizzle S128 = CU_TENSOR_MAP_SWIZZLE_128B, S64 = CU_TENSOR_MAP_SWIZZLE_64B;
    CUtensorMap a_x = make_map(enc, x, D_, S_, 64, 128, S128);
    CUtensorMap a_h = make_map(enc, p_h, D_, S_, 64, 128, S128);
    CUtensorMap a_x1 = make_map(enc, p_x1, D_, S_, 64, 128, S128);
    CUtensorMap a_hh = make_map(enc, p_hh, F_, S_, 64, 128, S128);
    CUtensorMap a_o = make_map(enc, p_o, D_, S_, 64, 128, S128);
    CUtensorMap b_qkv = make_map(enc, wqkv, 3 * D_, D_, 64, 64, S128);
    CUtensorMap b_w1 = make_map(enc, w1, D_, D_, 64, 64, S128);
    CUtensorMap b_w2 = make_map(enc, w2, D_, D_, 64, 64, S128);
    CUtensorMap b_w3 = make_map(enc, w3, F_, D_, 64, 64, S128);
    CUtensorMap b_w4 = make_map(enc, w4, D_, F_, 64, 64, S128);
    CUtensorMap b_wo = make_map(enc, wo, D_, D_, 64, 64, S128);
    CUtensorMap c_qkv = make_map(enc, p_qkv, 3 * D_, S_, 64, 64, S128);
    CUtensorMap c_h = make_map(enc, p_h, D_, S_, 64, 64, S128);
    CUtensorMap c_x1 = make_map(enc, p_x1, D_, S_, 64, 64, S128);
    CUtensorMap c_hh = make_map(enc, p_hh, F_, S_, 64, 64, S128);
    CUtensorMap c_out = make_map(enc, d_out, D_, S_, 64, 64, S128);
    CUtensorMap t_q = make_map(enc, p_qkv, 3 * D_, S_, 32, 64, S64);
    CUtensorMap t_kv = make_map(enc, p_qkv, 3 * D_, S_, 32, A_BKV, S64);

    cudaFuncSetAttribute(gemm_kernel<1>, cudaFuncAttributeMaxDynamicSharedMemorySize, G_SMEM);
    cudaFuncSetAttribute(gemm_kernel<2>, cudaFuncAttributeMaxDynamicSharedMemorySize, G_SMEM);
    cudaFuncSetAttribute(gemm_kernel<3>, cudaFuncAttributeMaxDynamicSharedMemorySize, G_SMEM);
    cudaFuncSetAttribute(gemm_kernel<4>, cudaFuncAttributeMaxDynamicSharedMemorySize, G_SMEM);
    cudaFuncSetAttribute(attn_kernel, cudaFuncAttributeMaxDynamicSharedMemorySize, A_SMEM);

    cudaStream_t st = cudaStreamPerThread;
    launch(prep_kernel, PREP_CS_BLOCKS + PREP_ROW_BLOCKS, 256, 0, st, false, x, gate_w, w1, w3);
    launch(gemm_kernel<1>, 16 * 32, 288, G_SMEM, st, true, a_x, a_x, b_qkv, b_w1, c_qkv, c_h, x);
    launch(attn_kernel, H_ * (S_ / A_BQ), A_THREADS, A_SMEM, st, true, t_q, t_kv);
    launch(gemm_kernel<2>, 16 * 8, 288, G_SMEM, st, true, a_h, a_h, b_w2, b_w2, c_x1, c_x1, x);
    launch(gemm_kernel<3>, 16 * 28, 288, G_SMEM, st, true, a_x1, a_x1, b_w3, b_w3, c_hh, c_hh, x);
    launch(gemm_kernel<4>, 16 * 8, 288, G_SMEM, st, true, a_hh, a_o, b_w4, b_wo, c_out, c_out, x);
}
```

```cpp
#include <cuda_runtime.h>
#include <cuda_bf16.h>
#include <cuda.h>
#include <stdint.h>

namespace {

constexpr int S_ = 2048;
constexpr int D_ = 1024;
constexpr int F_ = 3584;
constexpr int H_ = 32;
constexpr int DH_ = 32;

__device__ __align__(1024) __nv_bfloat16 g_qkv[S_ * 3 * D_];
__device__ __align__(1024) __nv_bfloat16 g_h[S_ * D_];
__device__ __align__(1024) __nv_bfloat16 g_x1[S_ * D_];
__device__ __align__(1024) __nv_bfloat16 g_hh[S_ * F_];
__device__ __align__(1024) __nv_bfloat16 g_o[S_ * D_];
__device__ __align__(16) float4 g_xstat[S_];
constexpr int CS_SPLIT = 8;
__device__ __align__(16) float g_cs[CS_SPLIT][D_ + F_];
__device__ __align__(16) float2 g_x1part[S_][8];

#define TL_START(k)
#define TL_END(k)
#define DBG_T(i)
#define DBG_G(i)

__device__ __forceinline__ uint32_t smem_u32(const void* p) {
    return (uint32_t)__cvta_generic_to_shared(p);
}
__device__ __forceinline__ void mbar_init(uint32_t bar, uint32_t count) {
    asm volatile("mbarrier.init.shared::cta.b64 [%0], %1;" ::"r"(bar), "r"(count) : "memory");
}
__device__ __forceinline__ void mbar_expect_tx(uint32_t bar, uint32_t bytes) {
    asm volatile("mbarrier.arrive.expect_tx.shared::cta.b64 _, [%0], %1;" ::"r"(bar), "r"(bytes) : "memory");
}
__device__ __forceinline__ void mbar_arrive(uint32_t bar) {
    asm volatile("mbarrier.arrive.shared::cta.b64 _, [%0];" ::"r"(bar) : "memory");
}
__device__ __forceinline__ void mbar_wait(uint32_t bar, uint32_t parity) {
    asm volatile(
        "{\n"
        ".reg .pred p;\n"
        "LAB_WAIT:\n"
        "mbarrier.try_wait.parity.shared::cta.b64 p, [%0], %1;\n"
        "@p bra LAB_DONE;\n"
        "bra LAB_WAIT;\n"
        "LAB_DONE:\n"
        "}\n" ::"r"(bar), "r"(parity) : "memory");
}
__device__ __forceinline__ void tma_load_2d(uint32_t dst, const CUtensorMap* map, int c0, int c1, uint32_t bar) {
    asm volatile(
        "cp.async.bulk.tensor.2d.shared::cluster.global.mbarrier::complete_tx::bytes [%0], [%1, {%3, %4}], [%2];"
        ::"r"(dst), "l"(reinterpret_cast<uint64_t>(map)), "r"(bar), "r"(c0), "r"(c1) : "memory");
}
__device__ __forceinline__ void tma_load_3d(uint32_t dst, const CUtensorMap* map, int c0, int c1, int c2, uint32_t bar) {
    asm volatile(
        "cp.async.bulk.tensor.3d.shared::cluster.global.mbarrier::complete_tx::bytes [%0], [%1, {%3, %4, %5}], [%2];"
        ::"r"(dst), "l"(reinterpret_cast<uint64_t>(map)), "r"(bar), "r"(c0), "r"(c1), "r"(c2) : "memory");
}
__device__ __forceinline__ void tma_store_2d(const CUtensorMap* map, uint32_t src, int c0, int c1) {
    asm volatile(
        "cp.async.bulk.tensor.2d.global.shared::cta.bulk_group [%0, {%2, %3}], [%1];"
        ::"l"(reinterpret_cast<uint64_t>(map)), "r"(src), "r"(c0), "r"(c1) : "memory");
}
__device__ __forceinline__ void bulk_load(uint32_t dst, const void* src, uint32_t bytes, uint32_t bar) {
    asm volatile("cp.async.bulk.shared::cluster.global.mbarrier::complete_tx::bytes [%0], [%1], %2, [%3];"
                 ::"r"(dst), "l"(src), "r"(bytes), "r"(bar) : "memory");
}
__device__ __forceinline__ void bulk_store(void* dst, uint32_t src, uint32_t bytes) {
    asm volatile("cp.async.bulk.global.shared::cta.bulk_group [%0], [%1], %2;" ::"l"(dst), "r"(src), "r"(bytes) : "memory");
}
__device__ __forceinline__ void tma_store_commit() { asm volatile("cp.async.bulk.commit_group;" ::: "memory"); }
__device__ __forceinline__ void tma_store_wait0() { asm volatile("cp.async.bulk.wait_group 0;" ::: "memory"); }
__device__ __forceinline__ void fence_proxy_async() { asm volatile("fence.proxy.async.shared::cta;" ::: "memory"); }
__device__ __forceinline__ void fence_mbar_init() { asm volatile("fence.mbarrier_init.release.cluster;" ::: "memory"); }
__device__ __forceinline__ void wgmma_fence() { asm volatile("wgmma.fence.sync.aligned;" ::: "memory"); }
__device__ __forceinline__ void wgmma_commit() { asm volatile("wgmma.commit_group.sync.aligned;" ::: "memory"); }
template <int N>
__device__ __forceinline__ void wgmma_wait() { asm volatile("wgmma.wait_group.sync.aligned %0;" ::"n"(N) : "memory"); }
template <int N>
__device__ __forceinline__ void fence_regs(float (&a)[N]) {
#pragma unroll
    for (int i = 0; i < N; i++) asm volatile("" : "+f"(a[i])::"memory");
}
__device__ __forceinline__ void named_bar_sync(int id, int n) { asm volatile("bar.sync %0, %1;" ::"r"(id), "r"(n) : "memory"); }
__device__ __forceinline__ void named_bar_arrive(int id, int n) { asm volatile("bar.arrive %0, %1;" ::"r"(id), "r"(n) : "memory"); }
__device__ __forceinline__ void pdl_wait() { asm volatile("griddepcontrol.wait;" ::: "memory"); }
__device__ __forceinline__ void pdl_launch() { asm volatile("griddepcontrol.launch_dependents;" ::: "memory"); }

__device__ __forceinline__ uint64_t make_desc(uint32_t addr, uint32_t lbo_bytes, uint32_t sbo_bytes, uint32_t layout) {
    uint64_t d = 0;
    d |= (uint64_t)((addr & 0x3FFFF) >> 4);
    d |= (uint64_t)((lbo_bytes >> 4) & 0x3FFF) << 16;
    d |= (uint64_t)((sbo_bytes >> 4) & 0x3FFF) << 32;
    d |= (uint64_t)layout << 62;
    return d;
}
constexpr uint32_t SW128 = 1, SW64 = 2;

__device__ __forceinline__ uint32_t pack_bf16(float lo, float hi) {
    uint32_t r;
    asm("cvt.rn.bf16x2.f32 %0, %1, %2;" : "=r"(r) : "f"(hi), "f"(lo));
    return r;
}
__device__ __forceinline__ float bf16_lo(uint32_t v) { return __uint_as_float(v << 16); }
__device__ __forceinline__ float bf16_hi(uint32_t v) { return __uint_as_float(v & 0xFFFF0000u); }
__device__ __forceinline__ float ex2(float x) {
    float r;
    asm("ex2.approx.ftz.f32 %0, %1;" : "=f"(r) : "f"(x));
    return r;
}
__device__ __forceinline__ float tanh_approx(float x) {
    float r;
    asm("tanh.approx.f32 %0, %1;" : "=f"(r) : "f"(x));
    return r;
}
__device__ __forceinline__ float gelu_tanh(float v) {
    float u = v * (0.7978845608028654f + 0.0356774081363001f * v * v);
    float hv = 0.5f * v;
    return fmaf(hv, tanh_approx(u), hv);
}
__device__ __forceinline__ void stmatrix_x4(uint32_t addr, uint32_t r0, uint32_t r1, uint32_t r2, uint32_t r3) {
    asm volatile("stmatrix.sync.aligned.m8n8.x4.shared.b16 [%0], {%1, %2, %3, %4};"
                 ::"r"(addr), "r"(r0), "r"(r1), "r"(r2), "r"(r3) : "memory");
}

#define ACC8(a, o) "+f"(a[o + 0]), "+f"(a[o + 1]), "+f"(a[o + 2]), "+f"(a[o + 3]), "+f"(a[o + 4]), "+f"(a[o + 5]), "+f"(a[o + 6]), "+f"(a[o + 7])

template <int TB>
__device__ __forceinline__ void wgmma_m64n128k16_ss(float (&d)[64], uint64_t da, uint64_t db, int scale_d) {
    asm volatile(
        "{\n"
        ".reg .pred p;\n"
        "setp.ne.b32 p, %66, 0;\n"
        "wgmma.mma_async.sync.aligned.m64n128k16.f32.bf16.bf16 "
        "{%0, %1, %2, %3, %4, %5, %6, %7, %8, %9, %10, %11, %12, %13, %14, %15, "
        "%16, %17, %18, %19, %20, %21, %22, %23, %24, %25, %26, %27, %28, %29, %30, %31, "
        "%32, %33, %34, %35, %36, %37, %38, %39, %40, %41, %42, %43, %44, %45, %46, %47, "
        "%48, %49, %50, %51, %52, %53, %54, %55, %56, %57, %58, %59, %60, %61, %62, %63}, "
        "%64, %65, p, 1, 1, 0, %67;\n"
        "}\n"
        : ACC8(d, 0), ACC8(d, 8), ACC8(d, 16), ACC8(d, 24), ACC8(d, 32), ACC8(d, 40), ACC8(d, 48), ACC8(d, 56)
        : "l"(da), "l"(db), "r"(scale_d), "n"(TB));
}

constexpr int PREP_ROW_BLOCKS = S_ / 8;
constexpr int PREP_CS_BLOCKS = (D_ / 256) * CS_SPLIT;

__device__ __forceinline__ float bf16_round(float v) { return __bfloat162float(__float2bfloat16_rn(v)); }

__global__ void __launch_bounds__(256) prep_kernel(const __nv_bfloat16* __restrict__ x,
                                                   const __nv_bfloat16* __restrict__ gate_w,
                                                   const __nv_bfloat16* __restrict__ w1,
                                                   const __nv_bfloat16* __restrict__ w3) {
    pdl_launch();
    TL_START(0);
    const int tid = threadIdx.x;
    if (blockIdx.x < PREP_CS_BLOCKS) {
        __shared__ float red[8][256];
        const int cb = blockIdx.x / CS_SPLIT, ks = blockIdx.x % CS_SPLIT;
        const __nv_bfloat16* w;
        int ld, col0;
        if (cb < D_ / 256) { w = w1; ld = D_; col0 = cb * 256; }
        else { w = w3; ld = F_; col0 = (cb - D_ / 256) * 256; }
        const int cg = tid & 31, rg = tid >> 5;
        const int row0 = ks * (D_ / CS_SPLIT) + rg * 16;
        float s[8];
#pragma unroll
        for (int i = 0; i < 8; i++) s[i] = 0.f;
        const uint4* p = reinterpret_cast<const uint4*>(w + (size_t)row0 * ld + col0 + cg * 8);
        uint4 v[16];
#pragma unroll
        for (int r = 0; r < 16; r++) v[r] = __ldg(p + (size_t)r * (ld / 8));
#pragma unroll
        for (int r = 0; r < 16; r++) {
            s[0] += bf16_lo(v[r].x); s[1] += bf16_hi(v[r].x);
            s[2] += bf16_lo(v[r].y); s[3] += bf16_hi(v[r].y);
            s[4] += bf16_lo(v[r].z); s[5] += bf16_hi(v[r].z);
            s[6] += bf16_lo(v[r].w); s[7] += bf16_hi(v[r].w);
        }
#pragma unroll
        for (int i = 0; i < 8; i++) red[rg][cg * 8 + i] = s[i];
        __syncthreads();
        float t = 0.f;
#pragma unroll
        for (int i = 0; i < 8; i++) t += red[i][tid];
        g_cs[ks][cb * 256 + tid] = t;
    } else {
        const int row = (blockIdx.x - PREP_CS_BLOCKS) * 8 + (tid >> 5);
        const int lane = tid & 31;
        const uint4* p = reinterpret_cast<const uint4*>(x + (size_t)row * D_);
        const uint4* gw = reinterpret_cast<const uint4*>(gate_w);
        float v[32];
        float sum = 0.f, dot = 0.f;
#pragma unroll
        for (int i = 0; i < 4; i++) {
            uint4 a = __ldg(p + i * 32 + lane);
            uint4 b = __ldg(gw + i * 32 + lane);
            v[i * 8 + 0] = bf16_lo(a.x); v[i * 8 + 1] = bf16_hi(a.x);
            v[i * 8 + 2] = bf16_lo(a.y); v[i * 8 + 3] = bf16_hi(a.y);
            v[i * 8 + 4] = bf16_lo(a.z); v[i * 8 + 5] = bf16_hi(a.z);
            v[i * 8 + 6] = bf16_lo(a.w); v[i * 8 + 7] = bf16_hi(a.w);
            dot += bf16_round(v[i * 8 + 0] * bf16_lo(b.x)) + bf16_round(v[i * 8 + 1] * bf16_hi(b.x));
            dot += bf16_round(v[i * 8 + 2] * bf16_lo(b.y)) + bf16_round(v[i * 8 + 3] * bf16_hi(b.y));
            dot += bf16_round(v[i * 8 + 4] * bf16_lo(b.z)) + bf16_round(v[i * 8 + 5] * bf16_hi(b.z));
            dot += bf16_round(v[i * 8 + 6] * bf16_lo(b.w)) + bf16_round(v[i * 8 + 7] * bf16_hi(b.w));
        }
#pragma unroll
        for (int i = 0; i < 32; i++) sum += v[i];
#pragma unroll
        for (int o = 16; o > 0; o >>= 1) {
            sum += __shfl_xor_sync(0xffffffffu, sum, o);
            dot += __shfl_xor_sync(0xffffffffu, dot, o);
        }
        const float mean = sum * (1.f / D_);
        float m2 = 0.f;
#pragma unroll
        for (int i = 0; i < 32; i++) { float d = v[i] - mean; m2 += d * d; }
#pragma unroll
        for (int o = 16; o > 0; o >>= 1) m2 += __shfl_xor_sync(0xffffffffu, m2, o);
        if (lane == 0) {
            float rstd = rsqrtf(m2 * (1.f / D_) + 1e-5f);
            const float logit = bf16_round(dot);
            const float g = bf16_round(1.f / (1.f + __expf(-logit)));
            const float og = bf16_round(1.f - g);
            g_xstat[row] = make_float4(mean, rstd, g, og);
        }
    }
    TL_END(0);
}

constexpr int BM = 128, BN = 128, BK = 64;
constexpr int A_STAGE_BYTES = BM * BK * 2;
constexpr int B_STAGE_BYTES = BK * BN * 2;
constexpr int STAGE_BYTES = A_STAGE_BYTES + B_STAGE_BYTES;
constexpr int KT_ITERS = 44;
__host__ __device__ constexpr int gemm_stages(int mode) { return mode == 6 ? 6 : (mode == 1 || mode == 5) ? 3 : 4; }
constexpr int gemm_smem(int mode) { return gemm_stages(mode) * STAGE_BYTES + 1024   + 1024  ; }

__host__ __device__ constexpr bool gemm_fold(int mode) { return mode >= 2 && mode <= 5; }
__host__ __device__ constexpr int gemm_threads(int mode) { return gemm_fold(mode) ? 256 : 288; }

template <int MODE>
__global__ void __launch_bounds__(288, 2)
gemm_kernel(const __grid_constant__ CUtensorMap tmA0, const __grid_constant__ CUtensorMap tmB0,
            const __grid_constant__ CUtensorMap tmC0, const __nv_bfloat16* __restrict__ xres,
            const __grid_constant__ CUtensorMap tmA1, const __grid_constant__ CUtensorMap tmB1) {
    constexpr int G_STAGES = gemm_stages(MODE);
    constexpr bool FOLD = gemm_fold(MODE);
    constexpr int NK = (MODE == 4) ? KT_ITERS : (MODE == 6) ? (F_ / BK - KT_ITERS) + D_ / BK : D_ / BK;

    extern __shared__ uint8_t smem_raw[];
    const uint32_t smem_base = (smem_u32(smem_raw) + 1023u) & ~1023u;
    uint8_t* smem_gen = smem_raw + (smem_base - smem_u32(smem_raw));
    const uint32_t bar_base = smem_base + G_STAGES * STAGE_BYTES;
    float* s_cs = reinterpret_cast<float*>(smem_gen + G_STAGES * STAGE_BYTES + 128);

    const int tid = threadIdx.x;
    const int wg = tid >> 7;
    TL_START(MODE);
    DBG_G(0);
    const int m_tile = blockIdx.x & 15;
    const int n_tile = blockIdx.x >> 4;
    const int m0 = m_tile * BM;
    const int n0 = n_tile * BN;

    if (tid == 0) {
#pragma unroll
        for (int s = 0; s < G_STAGES; s++) {
            mbar_init(bar_base + 8 * s, 1);
            mbar_init(bar_base + 8 * (G_STAGES + s), 8);
        }
        fence_mbar_init();
    }
    __syncthreads();

    auto issue_load = [&](int it, int part) {
        const int s = it % G_STAGES;
        const uint32_t ph = (it / G_STAGES) & 1;
        mbar_wait(bar_base + 8 * (G_STAGES + s), ph ^ 1);
        const uint32_t full = bar_base + 8 * s;
        if (part != 2) mbar_expect_tx(full, STAGE_BYTES);
        const uint32_t sa = smem_base + s * STAGE_BYTES;
        const uint32_t sb = sa + A_STAGE_BYTES;
        int ma = m0;
        if (MODE == 2) {
            const int q = it >> 2;
            ma += (q == 0) ? -1 : (q == 1) ? 1 : (q == 2) ? -2 : 2;
        }
        if (MODE == 6 && it >= D_ / BK) {
            const int k0 = (it - D_ / BK + KT_ITERS) * BK;
            if (part != 2) tma_load_2d(sa, &tmA1, k0, ma, full);
            if (part != 1) tma_load_3d(sb, &tmB1, 0, k0, n0 >> 6, full);
        } else {
            if (part != 2) tma_load_2d(sa, &tmA0, it * BK, ma, full);
            if (part != 1) tma_load_3d(sb, &tmB0, 0, it * BK, n0 >> 6, full);
        }
    };

    if (!FOLD && wg == 2) {
        if (tid == 256) {
            if (MODE != 1) pdl_wait();
            pdl_launch();
            for (int it = 0; it < NK; it++) issue_load(it, 0);
        }
    } else {
        const int cw = wg;
        const int warp = (tid >> 5) & 3;
        const int lane = tid & 31;
        if (FOLD) {
            if (tid == 0) {
                pdl_wait();
                for (int it = 0; it < G_STAGES; it++) issue_load(it, 1);
            } else if (tid == 128) {
                for (int it = 0; it < G_STAGES; it++) issue_load(it, 2);
            }
            __syncwarp();
        }
        float acc[64];
#pragma unroll
        for (int i = 0; i < 64; i++) acc[i] = 0.f;

        for (int it = 0; it < NK; it++) {
            const int s = it % G_STAGES;
            const uint32_t ph = (it / G_STAGES) & 1;
            mbar_wait(bar_base + 8 * s, ph);
            DBG_G(1 + it);
            const uint32_t sa = smem_base + s * STAGE_BYTES + cw * 8192;
            const uint32_t sb = smem_base + s * STAGE_BYTES + A_STAGE_BYTES;
            wgmma_fence();
#pragma unroll
            for (int k = 0; k < 4; k++) {
                uint64_t da = make_desc(sa + k * 32, 16, 1024, SW128);
                uint64_t db = make_desc(sb + k * 2048, 8192, 1024, SW128);
                wgmma_m64n128k16_ss<1>(acc, da, db, (it | k) != 0);
            }
            wgmma_commit();
            wgmma_wait<1>();
            if (it > 0 && lane == 0) mbar_arrive(bar_base + 8 * (G_STAGES + (it - 1) % G_STAGES));
            if (FOLD) {
                if ((tid & 127) == 0 && it > 0 && it - 1 + G_STAGES < NK) issue_load(it - 1 + G_STAGES, 1 + wg);
                __syncwarp();
            }
        }
        wgmma_wait<0>();
        DBG_G(20);
        if (FOLD && tid == 0) pdl_launch();

        if (MODE != 1) pdl_wait();
        const int r0 = m0 + cw * 64 + warp * 16 + (lane >> 2);
        const int r1 = r0 + 8;
        const int cq = (lane & 3) * 2;
        constexpr bool use_cs = (MODE == 3) || (MODE == 5);
        if (use_cs) {
            const int ct = tid;
            if (ct < BN) {
                const int col = (MODE == 5) ? (n0 + ct) : (D_ + n0 + ct);
                float t = 0.f;
#pragma unroll
                for (int i = 0; i < CS_SPLIT; i++) t += g_cs[i][col];
                s_cs[ct] = t;
            }
        }
        named_bar_sync(1, 256);

        if (MODE == 1) {
        } else if (MODE == 5) {
            const float4 st0 = g_xstat[r0], st1 = g_xstat[r1];
#pragma unroll
            for (int j = 0; j < 16; j++) {
                const float2 cs = *reinterpret_cast<const float2*>(&s_cs[j * 8 + cq]);
                acc[4 * j + 0] = gelu_tanh(st0.y * (acc[4 * j + 0] - st0.x * cs.x));
                acc[4 * j + 1] = gelu_tanh(st0.y * (acc[4 * j + 1] - st0.x * cs.y));
                acc[4 * j + 2] = gelu_tanh(st1.y * (acc[4 * j + 2] - st1.x * cs.x));
                acc[4 * j + 3] = gelu_tanh(st1.y * (acc[4 * j + 3] - st1.x * cs.y));
            }
        } else if (MODE == 2) {
            const uint32_t* x0 = reinterpret_cast<const uint32_t*>(xres + (size_t)r0 * D_ + n0 + cq);
            const uint32_t* x1 = reinterpret_cast<const uint32_t*>(xres + (size_t)r1 * D_ + n0 + cq);
            float s0 = 0.f, s1 = 0.f;
#pragma unroll
            for (int j = 0; j < 16; j++) {
                const uint32_t a = __ldg(x0 + j * 4), b = __ldg(x1 + j * 4);
                uint32_t p0 = pack_bf16(acc[4 * j + 0] + bf16_lo(a), acc[4 * j + 1] + bf16_hi(a));
                uint32_t p1 = pack_bf16(acc[4 * j + 2] + bf16_lo(b), acc[4 * j + 3] + bf16_hi(b));
                acc[4 * j + 0] = bf16_lo(p0); acc[4 * j + 1] = bf16_hi(p0);
                acc[4 * j + 2] = bf16_lo(p1); acc[4 * j + 3] = bf16_hi(p1);
                s0 += acc[4 * j + 0] + acc[4 * j + 1];
                s1 += acc[4 * j + 2] + acc[4 * j + 3];
            }
            s0 += __shfl_xor_sync(0xffffffffu, s0, 1); s0 += __shfl_xor_sync(0xffffffffu, s0, 2);
            s1 += __shfl_xor_sync(0xffffffffu, s1, 1); s1 += __shfl_xor_sync(0xffffffffu, s1, 2);
            const float mu0 = s0 * (1.f / BN), mu1 = s1 * (1.f / BN);
            float q0 = 0.f, q1 = 0.f;
#pragma unroll
            for (int j = 0; j < 16; j++) {
                float d;
                d = acc[4 * j + 0] - mu0; q0 += d * d;
                d = acc[4 * j + 1] - mu0; q0 += d * d;
                d = acc[4 * j + 2] - mu1; q1 += d * d;
                d = acc[4 * j + 3] - mu1; q1 += d * d;
            }
            q0 += __shfl_xor_sync(0xffffffffu, q0, 1); q0 += __shfl_xor_sync(0xffffffffu, q0, 2);
            q1 += __shfl_xor_sync(0xffffffffu, q1, 1); q1 += __shfl_xor_sync(0xffffffffu, q1, 2);
            if ((lane & 3) == 0) {
                g_x1part[r0][n_tile] = make_float2(s0, q0);
                g_x1part[r1][n_tile] = make_float2(s1, q1);
            }
        } else if (MODE == 3) {
            float mean[2], rstd[2], og[2];
#pragma unroll
            for (int h = 0; h < 2; h++) {
                const int r = h ? r1 : r0;
                const float4* pp = reinterpret_cast<const float4*>(&g_x1part[r][0]);
                float4 a = pp[0], b = pp[1], c = pp[2], d = pp[3];
                float tot = a.x + a.z + b.x + b.z + c.x + c.z + d.x + d.z;
                float mu = tot * (1.f / D_);
                float m2 = a.y + a.w + b.y + b.w + c.y + c.w + d.y + d.w;
                float e;
                e = a.x * (1.f / 128) - mu; m2 += 128.f * e * e;
                e = a.z * (1.f / 128) - mu; m2 += 128.f * e * e;
                e = b.x * (1.f / 128) - mu; m2 += 128.f * e * e;
                e = b.z * (1.f / 128) - mu; m2 += 128.f * e * e;
                e = c.x * (1.f / 128) - mu; m2 += 128.f * e * e;
                e = c.z * (1.f / 128) - mu; m2 += 128.f * e * e;
                e = d.x * (1.f / 128) - mu; m2 += 128.f * e * e;
                e = d.z * (1.f / 128) - mu; m2 += 128.f * e * e;
                mean[h] = mu;
                rstd[h] = rsqrtf(m2 * (1.f / D_) + 1e-5f);
                og[h] = g_xstat[r].w;
            }
#pragma unroll
            for (int j = 0; j < 16; j++) {
                const float2 cs = *reinterpret_cast<const float2*>(&s_cs[j * 8 + cq]);
                acc[4 * j + 0] = og[0] * gelu_tanh(rstd[0] * (acc[4 * j + 0] - mean[0] * cs.x));
                acc[4 * j + 1] = og[0] * gelu_tanh(rstd[0] * (acc[4 * j + 1] - mean[0] * cs.y));
                acc[4 * j + 2] = og[1] * gelu_tanh(rstd[1] * (acc[4 * j + 2] - mean[1] * cs.x));
                acc[4 * j + 3] = og[1] * gelu_tanh(rstd[1] * (acc[4 * j + 3] - mean[1] * cs.y));
            }
        } else {
            const float og0 = (MODE == 4) ? g_xstat[r0].w : 1.f, og1 = (MODE == 4) ? g_xstat[r1].w : 1.f;
            const __nv_bfloat16* add = (MODE == 4) ? g_x1 : g_h;
            const uint32_t* x0 = reinterpret_cast<const uint32_t*>(add + (size_t)r0 * D_ + n0 + cq);
            const uint32_t* x1 = reinterpret_cast<const uint32_t*>(add + (size_t)r1 * D_ + n0 + cq);
#pragma unroll
            for (int j = 0; j < 16; j++) {
                const uint32_t a = x0[j * 4], b = x1[j * 4];
                acc[4 * j + 0] += og0 * bf16_lo(a);
                acc[4 * j + 1] += og0 * bf16_hi(a);
                acc[4 * j + 2] += og1 * bf16_lo(b);
                acc[4 * j + 3] += og1 * bf16_hi(b);
            }
        }

        const uint32_t so = smem_base + cw * 16384;
        constexpr bool qkv_tile = (MODE == 1);
        {
            const int mrow = warp * 16 + (lane & 7) + ((lane >> 3) & 1) * 8;
            const int mcol = lane >> 4;
#pragma unroll
            for (int jj = 0; jj < 8; jj++) {
                uint32_t addr;
                if (qkv_tile) {
                    const int chunk = (jj & 1) * 2 + mcol;
                    addr = so + (jj >> 1) * 4096 + mrow * 64 + ((chunk ^ ((mrow >> 1) & 3)) << 4);
                } else {
                    const int chunk = (jj & 3) * 2 + mcol;
                    addr = so + (jj >> 2) * 8192 + mrow * 128 + ((chunk ^ (mrow & 7)) << 4);
                }
                stmatrix_x4(addr, pack_bf16(acc[8 * jj + 0], acc[8 * jj + 1]), pack_bf16(acc[8 * jj + 2], acc[8 * jj + 3]),
                            pack_bf16(acc[8 * jj + 4], acc[8 * jj + 5]), pack_bf16(acc[8 * jj + 6], acc[8 * jj + 7]));
            }
        }
        DBG_G(21);
        fence_proxy_async();
        named_bar_sync(2 + cw, 128);
        if ((tid & 127) == 0) {
            if (qkv_tile) {
#pragma unroll
                for (int hl = 0; hl < 4; hl++)
                    bulk_store(g_qkv + ((size_t)(n0 / 32 + hl) * S_ + m0 + cw * 64) * 32, so + hl * 4096, 4096);
            } else {
                tma_store_2d(&tmC0, so, n0, m0 + cw * 64);
                tma_store_2d(&tmC0, so + 8192, n0 + 64, m0 + cw * 64);
            }
            tma_store_commit();
            tma_store_wait0();
            if (MODE == 1) pdl_wait();
            DBG_G(22);
        }
    }
    TL_END(MODE);
}

constexpr int BIG_BN = 256;
constexpr int BIG_STAGES = 4;
constexpr int BIG_STAGE_BYTES = BM * BK * 2 + BK * BIG_BN * 2;
constexpr int BIG_SMEM = BIG_STAGES * BIG_STAGE_BYTES + 1024 + 2048;

__device__ __forceinline__ void wgmma_m64n256k16_ss(float (&d)[128], uint64_t da, uint64_t db, int scale_d) {
    asm volatile(
        "{\n"
        ".reg .pred p;\n"
        "setp.ne.b32 p, %130, 0;\n"
        "wgmma.mma_async.sync.aligned.m64n256k16.f32.bf16.bf16 "
        "{%0, %1, %2, %3, %4, %5, %6, %7, %8, %9, %10, %11, %12, %13, %14, %15, "
        "%16, %17, %18, %19, %20, %21, %22, %23, %24, %25, %26, %27, %28, %29, %30, %31, "
        "%32, %33, %34, %35, %36, %37, %38, %39, %40, %41, %42, %43, %44, %45, %46, %47, "
        "%48, %49, %50, %51, %52, %53, %54, %55, %56, %57, %58, %59, %60, %61, %62, %63, "
        "%64, %65, %66, %67, %68, %69, %70, %71, %72, %73, %74, %75, %76, %77, %78, %79, "
        "%80, %81, %82, %83, %84, %85, %86, %87, %88, %89, %90, %91, %92, %93, %94, %95, "
        "%96, %97, %98, %99, %100, %101, %102, %103, %104, %105, %106, %107, %108, %109, %110, %111, "
        "%112, %113, %114, %115, %116, %117, %118, %119, %120, %121, %122, %123, %124, %125, %126, %127}, "
        "%128, %129, p, 1, 1, 0, 1;\n"
        "}\n"
        : ACC8(d, 0), ACC8(d, 8), ACC8(d, 16), ACC8(d, 24), ACC8(d, 32), ACC8(d, 40), ACC8(d, 48), ACC8(d, 56),
          ACC8(d, 64), ACC8(d, 72), ACC8(d, 80), ACC8(d, 88), ACC8(d, 96), ACC8(d, 104), ACC8(d, 112), ACC8(d, 120)
        : "l"(da), "l"(db), "r"(scale_d));
}

__global__ void __launch_bounds__(288, 1)
gemm_big_kernel(const __grid_constant__ CUtensorMap tmA, const __grid_constant__ CUtensorMap tmBq,
                const __grid_constant__ CUtensorMap tmBh, const __grid_constant__ CUtensorMap tmCh,
                const __nv_bfloat16* __restrict__ w3) {
    constexpr int NK = D_ / BK;
    extern __shared__ uint8_t smem_raw[];
    const uint32_t smem_base = (smem_u32(smem_raw) + 1023u) & ~1023u;
    uint8_t* smem_gen = smem_raw + (smem_base - smem_u32(smem_raw));
    const uint32_t bar_base = smem_base + BIG_STAGES * BIG_STAGE_BYTES;
    float* s_cs = reinterpret_cast<float*>(smem_gen + BIG_STAGES * BIG_STAGE_BYTES + 128);

    const int tid = threadIdx.x;
    const int wg = tid >> 7;
    TL_START(1);
    const int m0 = (blockIdx.x & 15) * BM;
    const int n0 = (blockIdx.x >> 4) * BIG_BN;
    const bool is_h = n0 >= 3 * D_;

    if (tid == 0) {
#pragma unroll
        for (int s = 0; s < BIG_STAGES; s++) {
            mbar_init(bar_base + 8 * s, 1);
            mbar_init(bar_base + 8 * (BIG_STAGES + s), 8);
        }
        fence_mbar_init();
    }
    __syncthreads();

    if (wg == 2) {
        if (tid == 256) {
            pdl_launch();
            const CUtensorMap* pb = is_h ? &tmBh : &tmBq;
            const int nb = (is_h ? n0 - 3 * D_ : n0) >> 6;
            for (int it = 0; it < NK; it++) {
                const int s = it % BIG_STAGES;
                const uint32_t ph = (it / BIG_STAGES) & 1;
                mbar_wait(bar_base + 8 * (BIG_STAGES + s), ph ^ 1);
                const uint32_t full = bar_base + 8 * s;
                mbar_expect_tx(full, BIG_STAGE_BYTES);
                const uint32_t sa = smem_base + s * BIG_STAGE_BYTES;
                tma_load_2d(sa, &tmA, it * BK, m0, full);
                tma_load_3d(sa + A_STAGE_BYTES, pb, 0, it * BK, nb, full);
            }
        }
        __syncwarp();
        if (blockIdx.x < (F_ / 128) * CS_SPLIT) {
            const int lane = tid & 31;
            const int cb = blockIdx.x / CS_SPLIT, ks = blockIdx.x % CS_SPLIT;
            const int row0 = ks * (D_ / CS_SPLIT) + (lane >> 4) * 64;
            const uint4* p = reinterpret_cast<const uint4*>(w3 + (size_t)row0 * F_ + cb * 128 + (lane & 15) * 8);
            float sacc[8];
#pragma unroll
            for (int i = 0; i < 8; i++) sacc[i] = 0.f;
#pragma unroll 1
            for (int r0 = 0; r0 < 64; r0 += 16) {
                uint4 v[16];
#pragma unroll
                for (int r = 0; r < 16; r++) v[r] = __ldg(p + (size_t)(r0 + r) * (F_ / 8));
#pragma unroll
                for (int r = 0; r < 16; r++) {
                    sacc[0] += bf16_lo(v[r].x); sacc[1] += bf16_hi(v[r].x);
                    sacc[2] += bf16_lo(v[r].y); sacc[3] += bf16_hi(v[r].y);
                    sacc[4] += bf16_lo(v[r].z); sacc[5] += bf16_hi(v[r].z);
                    sacc[6] += bf16_lo(v[r].w); sacc[7] += bf16_hi(v[r].w);
                }
            }
#pragma unroll
            for (int i = 0; i < 8; i++) sacc[i] += __shfl_xor_sync(0xffffffffu, sacc[i], 16);
            if (lane < 16) {
                float4* dst = reinterpret_cast<float4*>(&g_cs[ks][D_ + cb * 128 + lane * 8]);
                dst[0] = make_float4(sacc[0], sacc[1], sacc[2], sacc[3]);
                dst[1] = make_float4(sacc[4], sacc[5], sacc[6], sacc[7]);
            }
        }
    } else {
        const int cw = wg;
        const int warp = (tid >> 5) & 3;
        const int lane = tid & 31;
        float acc[128];
#pragma unroll
        for (int i = 0; i < 128; i++) acc[i] = 0.f;
        for (int it = 0; it < NK; it++) {
            const int s = it % BIG_STAGES;
            const uint32_t ph = (it / BIG_STAGES) & 1;
            mbar_wait(bar_base + 8 * s, ph);
            const uint32_t sa = smem_base + s * BIG_STAGE_BYTES + cw * 8192;
            const uint32_t sb = smem_base + s * BIG_STAGE_BYTES + A_STAGE_BYTES;
            wgmma_fence();
#pragma unroll
            for (int k = 0; k < 4; k++) {
                uint64_t da = make_desc(sa + k * 32, 16, 1024, SW128);
                uint64_t db = make_desc(sb + k * 2048, 8192, 1024, SW128);
                wgmma_m64n256k16_ss(acc, da, db, (it | k) != 0);
            }
            wgmma_commit();
            wgmma_wait<1>();
            if (it > 0 && lane == 0) mbar_arrive(bar_base + 8 * (BIG_STAGES + (it - 1) % BIG_STAGES));
        }
        wgmma_wait<0>();

        const int r0 = m0 + cw * 64 + warp * 16 + (lane >> 2);
        const int r1 = r0 + 8;
        const int cq = (lane & 3) * 2;
        if (is_h) {
            pdl_wait();
            float t = 0.f;
#pragma unroll
            for (int i = 0; i < CS_SPLIT; i++) t += g_cs[i][n0 - 3 * D_ + tid];
            s_cs[tid] = t;
        }
        named_bar_sync(1, 256);
        if (is_h) {
            const float4 st0 = g_xstat[r0], st1 = g_xstat[r1];
#pragma unroll
            for (int j = 0; j < 32; j++) {
                const float2 cs = *reinterpret_cast<const float2*>(&s_cs[j * 8 + cq]);
                acc[4 * j + 0] = gelu_tanh(st0.y * (acc[4 * j + 0] - st0.x * cs.x));
                acc[4 * j + 1] = gelu_tanh(st0.y * (acc[4 * j + 1] - st0.x * cs.y));
                acc[4 * j + 2] = gelu_tanh(st1.y * (acc[4 * j + 2] - st1.x * cs.x));
                acc[4 * j + 3] = gelu_tanh(st1.y * (acc[4 * j + 3] - st1.x * cs.y));
            }
        }
        const uint32_t so = smem_base + cw * 32768;
        {
            const int mrow = warp * 16 + (lane & 7) + ((lane >> 3) & 1) * 8;
            const int mcol = lane >> 4;
#pragma unroll
            for (int jj = 0; jj < 16; jj++) {
                uint32_t addr;
                if (!is_h) {
                    const int chunk = (jj & 1) * 2 + mcol;
                    addr = so + (jj >> 1) * 4096 + mrow * 64 + ((chunk ^ ((mrow >> 1) & 3)) << 4);
                } else {
                    const int chunk = (jj & 3) * 2 + mcol;
                    addr = so + (jj >> 2) * 8192 + mrow * 128 + ((chunk ^ (mrow & 7)) << 4);
                }
                stmatrix_x4(addr, pack_bf16(acc[8 * jj + 0], acc[8 * jj + 1]), pack_bf16(acc[8 * jj + 2], acc[8 * jj + 3]),
                            pack_bf16(acc[8 * jj + 4], acc[8 * jj + 5]), pack_bf16(acc[8 * jj + 6], acc[8 * jj + 7]));
            }
        }
        fence_proxy_async();
        named_bar_sync(2 + cw, 128);
        if ((tid & 127) == 0) {
            if (!is_h) {
#pragma unroll
                for (int hl = 0; hl < 8; hl++)
                    bulk_store(g_qkv + ((size_t)(n0 / 32 + hl) * S_ + m0 + cw * 64) * 32, so + hl * 4096, 4096);
            } else {
#pragma unroll
                for (int q = 0; q < 4; q++) tma_store_2d(&tmCh, so + q * 8192, n0 - 3 * D_ + q * 64, m0 + cw * 64);
            }
            tma_store_commit();
            tma_store_wait0();
            if (!is_h) pdl_wait();
        }
    }
    TL_END(1);
}

constexpr int A_NWG = 2;
constexpr int A_BQ = 64 * A_NWG;
constexpr int A_BKV = 128;
constexpr int A_STAGES = 4;
constexpr int A_KV_BYTES = A_BKV * DH_ * 2;
constexpr int A_Q_BYTES = 64 * DH_ * 2;
constexpr int A_SMEM = 2 * A_NWG * A_Q_BYTES + (2 * A_STAGES + 1) * A_KV_BYTES + 1024 + 256;
constexpr int A_ITEMS = H_ * (S_ / A_BQ);
constexpr int A_THREADS = A_NWG * 128;

constexpr uint32_t A_DESC_HI = (512u >> 4) | (2u << 30);

template <int OFF>
__device__ __forceinline__ void wgmma_m64n40k16_rs(float (&d)[20], uint32_t a0, uint32_t a1, uint32_t a2, uint32_t a3,
                                                   uint32_t blo) {
    asm volatile(
        "{\n"
        ".reg .b32 lo;\n"
        ".reg .b64 db;\n"
        "add.s32 lo, %24, %25;\n"
        "mov.b64 db, {lo, %26};\n"
        "wgmma.mma_async.sync.aligned.m64n40k16.f32.bf16.bf16 "
        "{%0, %1, %2, %3, %4, %5, %6, %7, %8, %9, %10, %11, %12, %13, %14, %15, %16, %17, %18, %19}, "
        "{%20, %21, %22, %23}, db, 1, 1, 1, 1;\n"
        "}\n"
        : ACC8(d, 0), ACC8(d, 8), "+f"(d[16]), "+f"(d[17]), "+f"(d[18]), "+f"(d[19])
        : "r"(a0), "r"(a1), "r"(a2), "r"(a3), "r"(blo), "n"(OFF), "n"(A_DESC_HI));
}

template <int AOFF, int BOFF>
__device__ __forceinline__ void wgmma_qk(float (&d)[64], uint32_t alo, uint32_t blo, int scale_d) {
    asm volatile(
        "{\n"
        ".reg .b32 la, lb;\n"
        ".reg .b64 da, db;\n"
        ".reg .pred p;\n"
        "setp.ne.b32 p, %69, 0;\n"
        "add.s32 la, %64, %66;\n"
        "add.s32 lb, %65, %67;\n"
        "mov.b64 da, {la, %68};\n"
        "mov.b64 db, {lb, %68};\n"
        "wgmma.mma_async.sync.aligned.m64n128k16.f32.bf16.bf16 "
        "{%0, %1, %2, %3, %4, %5, %6, %7, %8, %9, %10, %11, %12, %13, %14, %15, "
        "%16, %17, %18, %19, %20, %21, %22, %23, %24, %25, %26, %27, %28, %29, %30, %31, "
        "%32, %33, %34, %35, %36, %37, %38, %39, %40, %41, %42, %43, %44, %45, %46, %47, "
        "%48, %49, %50, %51, %52, %53, %54, %55, %56, %57, %58, %59, %60, %61, %62, %63}, "
        "da, db, p, 1, 1, 0, 0;\n"
        "}\n"
        : ACC8(d, 0), ACC8(d, 8), ACC8(d, 16), ACC8(d, 24), ACC8(d, 32), ACC8(d, 40), ACC8(d, 48), ACC8(d, 56)
        : "r"(alo), "r"(blo), "n"(AOFF), "n"(BOFF), "n"(A_DESC_HI), "r"(scale_d));
}

struct AttnCtx {
    uint32_t dq, dk, dv;
    uint32_t bar_kf, bar_vf, bar_ke, bar_ve;
    uint32_t sK, sV;
    const __nv_bfloat16 *gK, *gKn;
    int lane, zero, wg;
    bool producer, has_next;
};

template <int ST>
__device__ __forceinline__ void attn_pump(const AttnCtx& c, uint32_t ph, int t) {
    constexpr int NT = S_ / A_BKV;
    constexpr size_t VOFF = (size_t)H_ * S_ * DH_;
    if (t + 4 < NT || c.has_next) {
        const __nv_bfloat16* src = (t + 4 < NT) ? c.gK + (size_t)(t + 4) * A_BKV * DH_ : c.gKn + (size_t)(t + 4 - NT) * A_BKV * DH_;
        mbar_wait(c.bar_ke + 8 * ST, ph);
        mbar_expect_tx(c.bar_kf + 8 * ST, A_KV_BYTES);
        bulk_load(c.sK + ST * A_KV_BYTES, src, A_KV_BYTES, c.bar_kf + 8 * ST);
    }
    if (t + 3 < NT || c.has_next) {
        constexpr int SV = (ST + 3) % A_STAGES;
        const __nv_bfloat16* src = (t + 3 < NT) ? c.gK + (size_t)(t + 3) * A_BKV * DH_ : c.gKn + (size_t)(t + 3 - NT) * A_BKV * DH_;
        mbar_wait(c.bar_ve + 8 * SV, (SV == 3) ? (ph ^ 1) : ph);
        mbar_expect_tx(c.bar_vf + 8 * SV, A_KV_BYTES);
        bulk_load(c.sV + SV * A_KV_BYTES, src + VOFF, A_KV_BYTES, c.bar_vf + 8 * SV);
    }
}
constexpr float A_CSCALE = 0.17677669529663687f * 1.4426950408889634f;

template <int ST>
__device__ __forceinline__ void attn_issue_qk(const AttnCtx& c, float (&sc)[64], uint32_t ph) {
    mbar_wait(c.bar_kf + 8 * ST, ph);
    wgmma_fence();
    wgmma_qk<0, (ST * A_KV_BYTES) / 16>(sc, c.dq, c.dk, c.zero);
    wgmma_qk<2, (ST * A_KV_BYTES + 32) / 16>(sc, c.dq, c.dk, 1);
    wgmma_commit();
}

template <int ST>
__device__ __forceinline__ void attn_issue_pv(const AttnCtx& c, float (&o)[20], const uint32_t (&p)[32], uint32_t ph) {
    mbar_wait(c.bar_vf + 8 * ST, ph);
    wgmma_fence();
    constexpr int SO = (ST * A_KV_BYTES) / 16 - (((ST * A_KV_BYTES) / 16) << 16);
    wgmma_m64n40k16_rs<SO + 0 * 64>(o, p[0], p[1], p[2], p[3], c.dv);
    wgmma_m64n40k16_rs<SO + 1 * 64>(o, p[4], p[5], p[6], p[7], c.dv);
    wgmma_m64n40k16_rs<SO + 2 * 64>(o, p[8], p[9], p[10], p[11], c.dv);
    wgmma_m64n40k16_rs<SO + 3 * 64>(o, p[12], p[13], p[14], p[15], c.dv);
    wgmma_m64n40k16_rs<SO + 4 * 64>(o, p[16], p[17], p[18], p[19], c.dv);
    wgmma_m64n40k16_rs<SO + 5 * 64>(o, p[20], p[21], p[22], p[23], c.dv);
    wgmma_m64n40k16_rs<SO + 6 * 64>(o, p[24], p[25], p[26], p[27], c.dv);
    wgmma_m64n40k16_rs<SO + 7 * 64>(o, p[28], p[29], p[30], p[31], c.dv);
    wgmma_commit();
}

template <bool SIGNAL>
__device__ __forceinline__ void attn_softmax(float (&sc)[64], float& m0v, float& m1v, float& al0, float& al1, int other_bar) {
    float a0 = fmaxf(sc[0], sc[1]), a1 = fmaxf(sc[2], sc[3]);
    float b0 = fmaxf(sc[4], sc[5]), b1 = fmaxf(sc[6], sc[7]);
#pragma unroll
    for (int j = 2; j < 16; j += 2) {
        a0 = fmaxf(a0, fmaxf(sc[4 * j + 0], sc[4 * j + 1]));
        a1 = fmaxf(a1, fmaxf(sc[4 * j + 2], sc[4 * j + 3]));
        b0 = fmaxf(b0, fmaxf(sc[4 * j + 4], sc[4 * j + 5]));
        b1 = fmaxf(b1, fmaxf(sc[4 * j + 6], sc[4 * j + 7]));
    }
    float mx0 = fmaxf(a0, b0), mx1 = fmaxf(a1, b1);
    mx0 = fmaxf(mx0, __shfl_xor_sync(0xffffffffu, mx0, 1));
    mx1 = fmaxf(mx1, __shfl_xor_sync(0xffffffffu, mx1, 1));
    mx0 = fmaxf(mx0, __shfl_xor_sync(0xffffffffu, mx0, 2));
    mx1 = fmaxf(mx1, __shfl_xor_sync(0xffffffffu, mx1, 2));
    const float mn0 = fmaxf(m0v, mx0), mn1 = fmaxf(m1v, mx1);
    al0 = ex2((m0v - mn0) * A_CSCALE);
    al1 = ex2((m1v - mn1) * A_CSCALE);
    m0v = mn0; m1v = mn1;
    const float mb0 = mn0 * A_CSCALE, mb1 = mn1 * A_CSCALE;
    if (SIGNAL) named_bar_arrive(other_bar, 256);
#pragma unroll
    for (int j = 0; j < 16; j++) {
        sc[4 * j + 0] = ex2(fmaf(sc[4 * j + 0], A_CSCALE, -mb0));
        sc[4 * j + 1] = ex2(fmaf(sc[4 * j + 1], A_CSCALE, -mb0));
        sc[4 * j + 2] = ex2(fmaf(sc[4 * j + 2], A_CSCALE, -mb1));
        sc[4 * j + 3] = ex2(fmaf(sc[4 * j + 3], A_CSCALE, -mb1));
    }
}

template <int ST>
__device__ __forceinline__ void attn_step(const AttnCtx& c, float (&sc)[64], float (&o)[20], uint32_t (&p)[32],
                                          float& m0v, float& m1v, float& al0, float& al1, uint32_t ph, int t) {
    constexpr int SN = (ST + 1) % A_STAGES;
    named_bar_sync(1 + c.wg, 256);
    attn_issue_qk<SN>(c, sc, (SN == 0) ? (ph ^ 1) : ph);
#pragma unroll
    for (int j = 0; j < 5; j++) {
        o[4 * j + 0] *= al0; o[4 * j + 1] *= al0;
        o[4 * j + 2] *= al1; o[4 * j + 3] *= al1;
    }
    attn_issue_pv<ST>(c, o, p, ph);
    wgmma_wait<1>();
    fence_regs(sc);
    if (c.lane == 0) mbar_arrive(c.bar_ke + 8 * SN);
    attn_softmax<true>(sc, m0v, m1v, al0, al1, 1 + (c.wg ^ 1));
    wgmma_wait<0>();
    fence_regs(o);
    if (c.lane == 0) mbar_arrive(c.bar_ve + 8 * ST);
    if (c.producer) attn_pump<ST>(c, ph, t);
    __syncwarp();
#pragma unroll
    for (int j = 0; j < 32; j++) p[j] = pack_bf16(sc[2 * j], sc[2 * j + 1]);
}

__global__ void __launch_bounds__(A_THREADS, 1)
attn_kernel() {
    extern __shared__ uint8_t smem_raw[];
    const uint32_t smem_base = (smem_u32(smem_raw) + 1023u) & ~1023u;
    uint8_t* smem_gen = smem_raw + (smem_base - smem_u32(smem_raw));
    const uint32_t sQ = smem_base;
    const uint32_t sK = sQ + 2 * A_NWG * A_Q_BYTES;
    const uint32_t sV = sK + A_STAGES * A_KV_BYTES;
    const uint32_t sOnes = sV + A_STAGES * A_KV_BYTES;
    const uint32_t bar = sOnes + A_KV_BYTES;
    const uint32_t bar_q = bar;
    const uint32_t bar_kf = bar + 16;
    const uint32_t bar_vf = bar_kf + 8 * A_STAGES;
    const uint32_t bar_ke = bar_vf + 8 * A_STAGES;
    const uint32_t bar_ve = bar_ke + 8 * A_STAGES;

    const int tid = threadIdx.x;
    TL_START(7);
    constexpr int NT = S_ / A_BKV;
    constexpr size_t HSTRIDE = (size_t)S_ * DH_;
    int item = blockIdx.x;

    if (tid == 0) {
        mbar_init(bar_q, 1);
        mbar_init(bar_q + 8, 1);
#pragma unroll
        for (int s = 0; s < A_STAGES; s++) {
            mbar_init(bar_kf + 8 * s, 1);
            mbar_init(bar_vf + 8 * s, 1);
            mbar_init(bar_ke + 8 * s, A_NWG * 4);
            mbar_init(bar_ve + 8 * s, A_NWG * 4);
        }
        fence_mbar_init();
        pdl_wait();
        pdl_launch();
        const __nv_bfloat16* gQ = g_qkv + (size_t)(item & 31) * HSTRIDE + (size_t)(item >> 5) * A_BQ * DH_;
        const __nv_bfloat16* gK = g_qkv + (size_t)(H_ + (item & 31)) * HSTRIDE;
        mbar_expect_tx(bar_q, A_NWG * A_Q_BYTES);
        bulk_load(sQ, gQ, A_NWG * A_Q_BYTES, bar_q);
#pragma unroll
        for (int t = 0; t < A_STAGES; t++) {
            mbar_expect_tx(bar_kf + 8 * t, A_KV_BYTES);
            bulk_load(sK + t * A_KV_BYTES, gK + (size_t)t * A_BKV * DH_, A_KV_BYTES, bar_kf + 8 * t);
            if (t < 3) {
                mbar_expect_tx(bar_vf + 8 * t, A_KV_BYTES);
                bulk_load(sV + t * A_KV_BYTES, gK + H_ * HSTRIDE + (size_t)t * A_BKV * DH_, A_KV_BYTES, bar_vf + 8 * t);
            }
        }
    }
    {
        uint4* po = reinterpret_cast<uint4*>(smem_gen + (sOnes - smem_base));
        const uint4 one4 = make_uint4(0x3F803F80u, 0x3F803F80u, 0x3F803F80u, 0x3F803F80u);
        for (int i = tid; i < A_KV_BYTES / 16; i += A_THREADS) po[i] = one4;
        fence_proxy_async();
    }
    __syncthreads();

    const int wg = tid >> 7;
    const int warp = (tid >> 5) & 3;
    AttnCtx c;
    c.dk = (uint32_t)make_desc(sK, 16, 512, SW64);
    c.dv = (uint32_t)make_desc(sV, sOnes - sV, 512, SW64);
    c.bar_kf = bar_kf; c.bar_vf = bar_vf; c.bar_ke = bar_ke; c.bar_ve = bar_ve;
    c.lane = tid & 31;
    c.sK = sK; c.sV = sV; c.producer = (tid == 0);
    c.zero = (int)blockDim.y - 1;
    c.wg = wg;
    if (wg == 1) named_bar_arrive(1, 256);
    float sc[64];
    uint32_t p[32];
#pragma unroll
    for (int i = 0; i < 64; i++) sc[i] = 0.f;

#pragma unroll 1
    for (int ii = 0; item < A_ITEMS; ii++, item += gridDim.x) {
        const int head = item & 31;
        const int q0 = (item >> 5) * A_BQ;
        const int nitem = item + gridDim.x;
        c.has_next = nitem < A_ITEMS;
        c.gK = g_qkv + (size_t)(H_ + head) * HSTRIDE;
        c.gKn = g_qkv + (size_t)(H_ + (nitem & 31)) * HSTRIDE;
        c.dq = (uint32_t)make_desc(sQ + (ii & 1) * A_NWG * A_Q_BYTES + wg * A_Q_BYTES, 16, 512, SW64);
        float o[20];
#pragma unroll
        for (int i = 0; i < 20; i++) o[i] = 0.f;
        float m0v = -INFINITY, m1v = -INFINITY, al0, al1;
        mbar_wait(bar_q + 8 * (ii & 1), (ii >> 1) & 1);
        attn_issue_qk<0>(c, sc, 0);
        wgmma_wait<0>();
        fence_regs(sc);
        if (c.lane == 0) mbar_arrive(bar_ke);
        attn_softmax<false>(sc, m0v, m1v, al0, al1, 0);
#pragma unroll
        for (int j = 0; j < 32; j++) p[j] = pack_bf16(sc[2 * j], sc[2 * j + 1]);
#pragma unroll 1
        for (int g = 0; g < NT / 4; g++) {
            const uint32_t ph = g & 1;
            attn_step<0>(c, sc, o, p, m0v, m1v, al0, al1, ph, 4 * g + 0);
            if (g == 2 && c.producer && c.has_next) {
                const uint32_t qb = bar_q + 8 * ((ii + 1) & 1);
                mbar_expect_tx(qb, A_NWG * A_Q_BYTES);
                bulk_load(sQ + ((ii + 1) & 1) * A_NWG * A_Q_BYTES,
                          g_qkv + (size_t)(nitem & 31) * HSTRIDE + (size_t)(nitem >> 5) * A_BQ * DH_, A_NWG * A_Q_BYTES, qb);
            }
            attn_step<1>(c, sc, o, p, m0v, m1v, al0, al1, ph, 4 * g + 1);
            attn_step<2>(c, sc, o, p, m0v, m1v, al0, al1, ph, 4 * g + 2);
            if (g < NT / 4 - 1) attn_step<3>(c, sc, o, p, m0v, m1v, al0, al1, ph, 4 * g + 3);
        }
#pragma unroll
        for (int j = 0; j < 5; j++) {
            o[4 * j + 0] *= al0; o[4 * j + 1] *= al0;
            o[4 * j + 2] *= al1; o[4 * j + 3] *= al1;
        }
        constexpr int SL = (NT - 1) % A_STAGES;
        constexpr uint32_t PL = ((NT - 1) / A_STAGES) & 1;
        attn_issue_pv<SL>(c, o, p, PL);
        wgmma_wait<0>();
        fence_regs(o);
        if (c.lane == 0) mbar_arrive(bar_ve + 8 * SL);
        if (c.producer) attn_pump<SL>(c, PL, NT - 1);
        __syncwarp();
        const int lane = c.lane;
        const int r0 = q0 + wg * 64 + warp * 16 + (lane >> 2);
        const int r1 = r0 + 8;
        const float f0 = g_xstat[r0].z / o[16], f1 = g_xstat[r1].z / o[18];
        uint32_t* d0 = reinterpret_cast<uint32_t*>(g_o + (size_t)r0 * D_ + head * DH_ + (lane & 3) * 2);
        uint32_t* d1 = reinterpret_cast<uint32_t*>(g_o + (size_t)r1 * D_ + head * DH_ + (lane & 3) * 2);
#pragma unroll
        for (int j = 0; j < 4; j++) {
            d0[j * 4] = pack_bf16(o[4 * j + 0] * f0, o[4 * j + 1] * f0);
            d1[j * 4] = pack_bf16(o[4 * j + 2] * f1, o[4 * j + 3] * f1);
        }
    }
    TL_END(7);
}

typedef CUresult (*PFN_encodeTiled)(CUtensorMap*, CUtensorMapDataType, cuuint32_t, void*, const cuuint64_t*,
                                    const cuuint64_t*, const cuuint32_t*, const cuuint32_t*, CUtensorMapInterleave,
                                    CUtensorMapSwizzle, CUtensorMapL2promotion, CUtensorMapFloatOOBfill);

CUtensorMap make_map(PFN_encodeTiled enc, const void* ptr, uint64_t inner, uint64_t outer, uint32_t box_inner,
                     uint32_t box_outer, CUtensorMapSwizzle sw) {
    CUtensorMap m;
    cuuint64_t dims[2] = {inner, outer};
    cuuint64_t strides[1] = {inner * 2};
    cuuint32_t box[2] = {box_inner, box_outer};
    cuuint32_t es[2] = {1, 1};
    enc(&m, CU_TENSOR_MAP_DATA_TYPE_BFLOAT16, 2, const_cast<void*>(ptr), dims, strides, box, es,
        CU_TENSOR_MAP_INTERLEAVE_NONE, sw, CU_TENSOR_MAP_L2_PROMOTION_L2_256B, CU_TENSOR_MAP_FLOAT_OOB_FILL_NONE);
    return m;
}

CUtensorMap make_map_w(PFN_encodeTiled enc, const void* ptr, uint64_t N, uint64_t K, uint32_t nbox) {
    CUtensorMap m;
    cuuint64_t dims[3] = {64, K, N / 64};
    cuuint64_t strides[2] = {N * 2, 128};
    cuuint32_t box[3] = {64, 64, nbox};
    cuuint32_t es[3] = {1, 1, 1};
    enc(&m, CU_TENSOR_MAP_DATA_TYPE_BFLOAT16, 3, const_cast<void*>(ptr), dims, strides, box, es,
        CU_TENSOR_MAP_INTERLEAVE_NONE, CU_TENSOR_MAP_SWIZZLE_128B, CU_TENSOR_MAP_L2_PROMOTION_L2_256B,
        CU_TENSOR_MAP_FLOAT_OOB_FILL_NONE);
    return m;
}

template <typename... KArgs, typename... Args>
void launch(void (*kern)(KArgs...), int grid, int block, int smem, cudaStream_t st, bool pdl, int cluster, Args&&... args) {
    cudaLaunchConfig_t cfg = {};
    cfg.gridDim = dim3(grid);
    cfg.blockDim = dim3(block);
    cfg.dynamicSmemBytes = smem;
    cfg.stream = st;
    cudaLaunchAttribute at[2];
    int na = 0;
    if (pdl) {
        at[na].id = cudaLaunchAttributeProgrammaticStreamSerialization;
        at[na].val.programmaticStreamSerializationAllowed = 1;
        na++;
    }
    if (cluster > 1) {
        at[na].id = cudaLaunchAttributeClusterDimension;
        at[na].val.clusterDim.x = cluster;
        at[na].val.clusterDim.y = 1;
        at[na].val.clusterDim.z = 1;
        na++;
    }
    cfg.attrs = at;
    cfg.numAttrs = na;
    cudaLaunchKernelEx(&cfg, kern, KArgs(args)...);
}

}

extern "C" void kernel_launch(void* const* d_in, const int* in_sizes, int n_in, void* d_out, int out_size) {
    const __nv_bfloat16* x = (const __nv_bfloat16*)d_in[0];
    const __nv_bfloat16* wqkv = (const __nv_bfloat16*)d_in[1];
    const __nv_bfloat16* wo = (const __nv_bfloat16*)d_in[2];
    const __nv_bfloat16* w1 = (const __nv_bfloat16*)d_in[4];
    const __nv_bfloat16* w2 = (const __nv_bfloat16*)d_in[5];
    const __nv_bfloat16* w3 = (const __nv_bfloat16*)d_in[6];
    const __nv_bfloat16* w4 = (const __nv_bfloat16*)d_in[7];
    const __nv_bfloat16* gate_w = (const __nv_bfloat16*)d_in[8];

    void* fn = nullptr;
    cudaDriverEntryPointQueryResult qres;
    cudaGetDriverEntryPoint("cuTensorMapEncodeTiled", &fn, cudaEnableDefault, &qres);
    PFN_encodeTiled enc = (PFN_encodeTiled)fn;

    void *p_h, *p_x1, *p_hh, *p_o;
    cudaGetSymbolAddress(&p_h, g_h);
    cudaGetSymbolAddress(&p_x1, g_x1);
    cudaGetSymbolAddress(&p_hh, g_hh);
    cudaGetSymbolAddress(&p_o, g_o);

    const CUtensorMapSwizzle S128 = CU_TENSOR_MAP_SWIZZLE_128B;
    CUtensorMap a_x = make_map(enc, x, D_, S_, 64, 128, S128);
    CUtensorMap a_h = make_map(enc, p_h, D_, S_, 64, 128, S128);
    CUtensorMap a_x1 = make_map(enc, p_x1, D_, S_, 64, 128, S128);
    CUtensorMap a_hh = make_map(enc, p_hh, F_, S_, 64, 128, S128);
    CUtensorMap a_o = make_map(enc, p_o, D_, S_, 64, 128, S128);
    CUtensorMap b_qkv4 = make_map_w(enc, wqkv, 3 * D_, D_, 4);
    CUtensorMap b_w14 = make_map_w(enc, w1, D_, D_, 4);
    CUtensorMap b_w2 = make_map_w(enc, w2, D_, D_, 2);
    CUtensorMap b_w3 = make_map_w(enc, w3, F_, D_, 2);
    CUtensorMap b_w4 = make_map_w(enc, w4, D_, F_, 2);
    CUtensorMap b_wo = make_map_w(enc, wo, D_, D_, 2);
    CUtensorMap c_h = make_map(enc, p_h, D_, S_, 64, 64, S128);
    CUtensorMap c_x1 = make_map(enc, p_x1, D_, S_, 64, 64, S128);
    CUtensorMap c_hh = make_map(enc, p_hh, F_, S_, 64, 64, S128);
    CUtensorMap c_out = make_map(enc, d_out, D_, S_, 64, 64, S128);

    cudaFuncSetAttribute(gemm_kernel<2>, cudaFuncAttributeMaxDynamicSharedMemorySize, gemm_smem(2));
    cudaFuncSetAttribute(gemm_kernel<3>, cudaFuncAttributeMaxDynamicSharedMemorySize, gemm_smem(3));
    cudaFuncSetAttribute(gemm_kernel<4>, cudaFuncAttributeMaxDynamicSharedMemorySize, gemm_smem(4));
    cudaFuncSetAttribute(gemm_kernel<6>, cudaFuncAttributeMaxDynamicSharedMemorySize, gemm_smem(6));
    cudaFuncSetAttribute(gemm_big_kernel, cudaFuncAttributeMaxDynamicSharedMemorySize, BIG_SMEM);
    cudaFuncSetAttribute(attn_kernel, cudaFuncAttributeMaxDynamicSharedMemorySize, A_SMEM);
    cudaFuncSetAttribute(attn_kernel, cudaFuncAttributePreferredSharedMemoryCarveout, cudaSharedmemCarveoutMaxShared);
    cudaFuncSetAttribute(gemm_kernel<2>, cudaFuncAttributePreferredSharedMemoryCarveout, cudaSharedmemCarveoutMaxShared);
    cudaFuncSetAttribute(gemm_kernel<3>, cudaFuncAttributePreferredSharedMemoryCarveout, cudaSharedmemCarveoutMaxShared);
    cudaFuncSetAttribute(gemm_kernel<4>, cudaFuncAttributePreferredSharedMemoryCarveout, cudaSharedmemCarveoutMaxShared);

    static int n_sm = 0;
    if (!n_sm) cudaDeviceGetAttribute(&n_sm, cudaDevAttrMultiProcessorCount, 0);
    static cudaStream_t s1 = nullptr;
    static cudaEvent_t e_fork = nullptr, e_join = nullptr;
    if (!s1) {
        int lo = 0, hi = 0;
        cudaDeviceGetStreamPriorityRange(&lo, &hi);
        cudaStreamCreateWithPriority(&s1, cudaStreamNonBlocking, hi);
        cudaEventCreateWithFlags(&e_fork, cudaEventDisableTiming);
        cudaEventCreateWithFlags(&e_join, cudaEventDisableTiming);
    }
    cudaStream_t st = cudaStreamPerThread;
    launch(prep_kernel, PREP_CS_BLOCKS + PREP_ROW_BLOCKS, 256, 0, st, false, 1, x, gate_w, w1, w3);
    launch(gemm_big_kernel, 16 * 16, 288, BIG_SMEM, st, true, 1, a_x, b_qkv4, b_w14, c_h, w3);
    cudaEventRecord(e_fork, st);
    launch(attn_kernel, n_sm, A_THREADS, A_SMEM, st, false, 1);
    cudaStreamWaitEvent(s1, e_fork, 0);
    launch(gemm_kernel<2>, 16 * 8, gemm_threads(2), gemm_smem(2), s1, false, 1, a_h, b_w2, c_x1, x, a_h, b_w2);
    launch(gemm_kernel<3>, 16 * 28, gemm_threads(3), gemm_smem(3), s1, true, 1, a_x1, b_w3, c_hh, x, a_h, b_w2);
    launch(gemm_kernel<4>, 16 * 8, gemm_threads(4), gemm_smem(4), s1, true, 1, a_hh, b_w4, c_h, x, a_h, b_w2);
    cudaEventRecord(e_join, s1);
    cudaStreamWaitEvent(st, e_join, 0);
    launch(gemm_kernel<6>, 16 * 8, gemm_threads(6), gemm_smem(6), st, false, 1, a_o, b_wo, c_out, x, a_hh, b_w4);
}
```
